```python
import torch

def _softmax(x, axis=-1):
    return torch.softmax(x, dim=axis)
def _gelu(x):
    return torch.nn.functional.gelu(x, approximate="tanh")
def _silu(x):
    return torch.nn.functional.silu(x)
def _sigmoid(x):
    return torch.sigmoid(x)
def _layernorm(x, axis=-1, eps=1e-5):
    m = x.mean(dim=axis, keepdim=True)
    v = x.var(dim=axis, keepdim=True, unbiased=False)
    return (x - m) / torch.sqrt(v + eps)
def _scatter_add(tgt, idx, src, axis=0):
    return tgt.clone().index_add_(axis, idx, src)
def _segment_sum(src, seg, n):
    out = torch.zeros((n,) + src.shape[1:], dtype=src.dtype)
    return out.index_add_(0, seg, src)
def _pad(x, pw):
    flat = tuple(v for pair in reversed(pw) for v in pair)
    return torch.nn.functional.pad(x, flat)

kernel_name = 'concat_heads__sliding_block_cached__sliding_block_cached__decode'

def setup_inputs():

    _w = (lambda a: (lambda t: t.to(torch.bfloat16) if t.is_floating_point() else t)(torch.as_tensor(a)))
    def _A_setup():
        B, Sq, D = 2, 1, 512
        Hq, Hkv, Sk, Dh = 32, 32, 8192, 128
        assert Hq % Hkv == 0, (Hq, Hkv)
        return {
            "x": _w((lambda *s: torch.randn(*s, dtype=torch.bfloat16) * 0.8)(B, Sq, D)),
            "k_cache": _w((lambda *s: torch.randn(*s, dtype=torch.bfloat16) * 1.6)(B, Hkv, Sk, Dh)),
            "v_cache": _w((lambda *s: torch.randn(*s, dtype=torch.bfloat16) * 0.2)(B, Hkv, Sk, Dh)),
            "wq": _w((lambda *s: torch.randn(*s, dtype=torch.bfloat16) * 1.6)(D, Hq * Dh) * (D ** -0.5)),
            "wo": _w((lambda *s: torch.randn(*s, dtype=torch.bfloat16) * 0.2)(Hq * Dh, D) * ((Hq * Dh) ** -0.5)),
        }
    _A_in = _A_setup()

    def _B_setup():
        B, Sq, D = 2, 1, 512
        Hq, Hkv, Sk, Dh = 32, 32, 8192, 128
        assert Hq % Hkv == 0, (Hq, Hkv)
        return {
            "x": _w((lambda *s: torch.randn(*s, dtype=torch.bfloat16) * 0.8)(B, Sq, D)),
            "k_cache": _w((lambda *s: torch.randn(*s, dtype=torch.bfloat16) * 1.6)(B, Hkv, Sk, Dh)),
            "v_cache": _w((lambda *s: torch.randn(*s, dtype=torch.bfloat16) * 0.2)(B, Hkv, Sk, Dh)),
            "wq": _w((lambda *s: torch.randn(*s, dtype=torch.bfloat16) * 1.6)(D, Hq * Dh) * (D ** -0.5)),
            "wo": _w((lambda *s: torch.randn(*s, dtype=torch.bfloat16) * 0.2)(Hq * Dh, D) * ((Hq * Dh) ** -0.5)),
        }
    _B_in = _B_setup()

    return {
        "A_x": _A_in["x"],
        "A_k_cache": _A_in["k_cache"],
        "A_v_cache": _A_in["v_cache"],
        "A_wq": _A_in["wq"],
        "A_wo": _A_in["wo"],
        "B_x": _B_in["x"],
        "B_k_cache": _B_in["k_cache"],
        "B_v_cache": _B_in["v_cache"],
        "B_wq": _B_in["wq"],
        "B_wo": _B_in["wo"],
    }

def reference(A_x, A_k_cache, A_v_cache, A_wq, A_wo, B_x, B_k_cache, B_v_cache, B_wq, B_wo):
    def _A_ref(x, k_cache, v_cache, wq, wo):
        B, Sq, D = x.shape
        Hq, Dh = 32, 128
        Hkv, Sk = k_cache.shape[1], k_cache.shape[2]
        W = min(4096, max(256, Sk // 4))
        rep = Hq // Hkv
        q = (lambda x, *d: x.permute(*d))((x @ wq).reshape(B, Sq, Hq, Dh), 0, 2, 1, 3)
        k = (lambda x, n, axis: torch.repeat_interleave(x, n, dim=axis))(k_cache[:, :, Sk - W:, :], rep, axis=1)
        v = (lambda x, n, axis: torch.repeat_interleave(x, n, dim=axis))(v_cache[:, :, Sk - W:, :], rep, axis=1)
        scores = torch.einsum("bhqd,bhkd->bhqk", q, k) * (Dh ** -0.5)
        p = _softmax(scores, axis=-1)
        o = torch.einsum("bhqk,bhkd->bhqd", p, v)
        return (lambda x, *d: x.permute(*d))(o, 0, 2, 1, 3).reshape(B, Sq, Hq * Dh) @ wo

    def _B_ref(x, k_cache, v_cache, wq, wo):
        B, Sq, D = x.shape
        Hq, Dh = 32, 128
        Hkv, Sk = k_cache.shape[1], k_cache.shape[2]
        W = min(4096, max(256, Sk // 4))
        rep = Hq // Hkv
        q = (lambda x, *d: x.permute(*d))((x @ wq).reshape(B, Sq, Hq, Dh), 0, 2, 1, 3)
        k = (lambda x, n, axis: torch.repeat_interleave(x, n, dim=axis))(k_cache[:, :, Sk - W:, :], rep, axis=1)
        v = (lambda x, n, axis: torch.repeat_interleave(x, n, dim=axis))(v_cache[:, :, Sk - W:, :], rep, axis=1)
        scores = torch.einsum("bhqd,bhkd->bhqk", q, k) * (Dh ** -0.5)
        p = _softmax(scores, axis=-1)
        o = torch.einsum("bhqk,bhkd->bhqd", p, v)
        return (lambda x, *d: x.permute(*d))(o, 0, 2, 1, 3).reshape(B, Sq, Hq * Dh) @ wo

    a = _A_ref(A_x, A_k_cache, A_v_cache, A_wq, A_wo)
    b = _B_ref(B_x, B_k_cache, B_v_cache, B_wq, B_wo)
    return torch.concatenate([a, b], axis=-1)
```

```cpp
#include <cuda_runtime.h>
#include <cuda_bf16.h>
#include <stdint.h>

namespace {

constexpr int D_MODEL = 512;
constexpr int NH = 32;
constexpr int SK = 8192;
constexpr int DH = 128;
constexpr int WIN = 2048;
constexpr int ROW_BYTES = DH * 2;
constexpr int CHUNK_BYTES = 32768;
constexpr int NSTAGES = 6;
constexpr int KCHUNKS = WIN * ROW_BYTES / CHUNK_BYTES;
constexpr int WO_BYTES = 64 * D_MODEL * 2;
constexpr int WOCHUNKS = WO_BYTES / CHUNK_BYTES;
constexpr int WO_ROWS_PER_CHUNK = CHUNK_BYTES / (D_MODEL * 2);
constexpr int NCW = 8;
constexpr int NCT = NCW * 32;
constexpr int NTHREADS = NCT + 32;

constexpr int SM_RING = 0;
constexpr int SM_RED = NSTAGES * CHUNK_BYTES;
constexpr int SM_QX = SM_RED + NCW * 256 * 4;
constexpr int SM_QS = SM_QX + 128 * 4;
constexpr int SM_OX = SM_QS + 128 * 2;
constexpr int SM_WMAX = SM_OX + 128 * 4;
constexpr int SM_WSUM = SM_WMAX + 32;
constexpr int SM_BARS = SM_WSUM + 32;
constexpr int SM_TOTAL = SM_BARS + (2 * NSTAGES + 2) * 8;

struct Params {
    const __nv_bfloat16* x[2];
    const __nv_bfloat16* k[2];
    const __nv_bfloat16* v[2];
    const __nv_bfloat16* wq[2];
    const __nv_bfloat16* wo[2];
    __nv_bfloat16* out;
};

__device__ uint32_t g_part[2 * 64 * 64 * 16];

__device__ __forceinline__ uint32_t smem_u32(const void* p) { return (uint32_t)__cvta_generic_to_shared(p); }
__device__ __forceinline__ void mbar_init(uint32_t bar, uint32_t cnt) {
    asm volatile("mbarrier.init.shared::cta.b64 [%0], %1;" ::"r"(bar), "r"(cnt) : "memory");
}
__device__ __forceinline__ void mbar_expect_tx(uint32_t bar, uint32_t bytes) {
    asm volatile("mbarrier.arrive.expect_tx.shared::cta.b64 _, [%0], %1;" ::"r"(bar), "r"(bytes) : "memory");
}
__device__ __forceinline__ void mbar_arrive(uint32_t bar) {
    asm volatile("mbarrier.arrive.shared::cta.b64 _, [%0];" ::"r"(bar) : "memory");
}
constexpr int SPIN_LIMIT = 1 << 22;
__device__ __forceinline__ bool mbar_try(uint32_t bar, uint32_t parity) {
    uint32_t ok;
    asm volatile(
        "{\n"
        ".reg .pred p;\n"
        "mbarrier.try_wait.parity.shared::cta.b64 p, [%1], %2;\n"
        "selp.u32 %0, 1, 0, p;\n"
        "}\n"
        : "=r"(ok)
        : "r"(bar), "r"(parity)
        : "memory");
    return ok != 0;
}
__device__ __forceinline__ bool mbar_try_cluster(uint32_t bar, uint32_t parity) {
    uint32_t ok;
    asm volatile(
        "{\n"
        ".reg .pred p;\n"
        "mbarrier.try_wait.parity.acquire.cluster.shared::cta.b64 p, [%1], %2;\n"
        "selp.u32 %0, 1, 0, p;\n"
        "}\n"
        : "=r"(ok)
        : "r"(bar), "r"(parity)
        : "memory");
    return ok != 0;
}
__device__ __forceinline__ void mbar_wait(uint32_t bar, uint32_t parity) {
    if (mbar_try(bar, parity)) return;
#pragma unroll 1
    for (int i = 0; i < SPIN_LIMIT; i++)
        if (mbar_try(bar, parity)) return;
    __trap();
}
__device__ __forceinline__ void mbar_wait_cluster(uint32_t bar, uint32_t parity) {
#pragma unroll 1
    for (int i = 0; i < SPIN_LIMIT; i++)
        if (mbar_try_cluster(bar, parity)) return;
    __trap();
}
__device__ __forceinline__ void bulk_load(uint32_t dst, const void* src, uint32_t bytes, uint32_t bar, uint64_t pol) {
    asm volatile(
        "cp.async.bulk.shared::cluster.global.mbarrier::complete_tx::bytes.L2::cache_hint [%0], [%1], %2, [%3], %4;" ::"r"(dst),
        "l"(src), "r"(bytes), "r"(bar), "l"(pol)
        : "memory");
}
__device__ __forceinline__ uint32_t mapa(uint32_t addr, uint32_t rank) {
    uint32_t r;
    asm volatile("mapa.shared::cluster.u32 %0, %1, %2;" : "=r"(r) : "r"(addr), "r"(rank));
    return r;
}
__device__ __forceinline__ void st_async_f32(uint32_t raddr, float v, uint32_t rbar) {
    asm volatile("st.async.shared::cluster.mbarrier::complete_tx::bytes.f32 [%0], %1, [%2];" ::"r"(raddr), "f"(v), "r"(rbar)
                 : "memory");
}
__device__ __forceinline__ void consumer_bar() { asm volatile("bar.sync 1, %0;" ::"n"(NCT) : "memory"); }
__device__ __forceinline__ uint4 lds128(uint32_t a) {
    uint4 v;
    asm volatile("ld.shared.v4.u32 {%0,%1,%2,%3}, [%4];" : "=r"(v.x), "=r"(v.y), "=r"(v.z), "=r"(v.w) : "r"(a));
    return v;
}
__device__ __forceinline__ uint32_t lds32(uint32_t a) {
    uint32_t v;
    asm volatile("ld.shared.u32 %0, [%1];" : "=r"(v) : "r"(a));
    return v;
}
__device__ __forceinline__ void ldsm_x4_trans(uint32_t a, uint32_t& r0, uint32_t& r1, uint32_t& r2, uint32_t& r3) {
    asm volatile("ldmatrix.sync.aligned.m8n8.x4.trans.shared.b16 {%0,%1,%2,%3}, [%4];"
                 : "=r"(r0), "=r"(r1), "=r"(r2), "=r"(r3)
                 : "r"(a));
}
__device__ __forceinline__ void mma_bf16(float (&c)[4], uint32_t a0, uint32_t a1, uint32_t a2, uint32_t a3, uint32_t b0,
                                         uint32_t b1) {
    asm volatile(
        "mma.sync.aligned.m16n8k16.row.col.f32.bf16.bf16.f32 {%0,%1,%2,%3}, {%4,%5,%6,%7}, {%8,%9}, {%0,%1,%2,%3};"
        : "+f"(c[0]), "+f"(c[1]), "+f"(c[2]), "+f"(c[3])
        : "r"(a0), "r"(a1), "r"(a2), "r"(a3), "r"(b0), "r"(b1));
}
__device__ __forceinline__ uint4 ldg_stream(const void* p, uint64_t pol) {
    uint4 v;
    asm volatile("ld.global.nc.L1::no_allocate.L2::cache_hint.v4.u32 {%0,%1,%2,%3}, [%4], %5;"
                 : "=r"(v.x), "=r"(v.y), "=r"(v.z), "=r"(v.w)
                 : "l"(p), "l"(pol));
    return v;
}
__device__ __forceinline__ float bf_lo(uint32_t w) { return __uint_as_float(w << 16); }
__device__ __forceinline__ float bf_hi(uint32_t w) { return __uint_as_float(w & 0xffff0000u); }
__device__ __forceinline__ float bf16_round(float v) { return __bfloat162float(__float2bfloat16_rn(v)); }
__device__ __forceinline__ uint32_t bf16_bits(float v) { return (uint32_t)__bfloat16_as_ushort(__float2bfloat16_rn(v)); }
__device__ __forceinline__ uint32_t enc(float v) {
    uint32_t b = __float_as_uint(v);
    if (b == 0xffffffffu) b = 0x7fffffffu;
    return ~b;
}

__global__ void __cluster_dims__(2, 1, 1) __launch_bounds__(NTHREADS, 1) fused_decode_kernel(const __grid_constant__ Params p) {
    extern __shared__ __align__(1024) unsigned char smem[];
    const uint32_t sbase = smem_u32(smem);
    const int cta = blockIdx.x;
    const int rank = cta & 1;
    const int pair = cta >> 1;
    const int br = pair >> 5;
    const int h = pair & 31;
    const int tid = threadIdx.x;
    const int warp = tid >> 5;
    const int lane = tid & 31;
    const uint32_t bar_full = sbase + SM_BARS;
    const uint32_t bar_empty = bar_full + NSTAGES * 8;
    const uint32_t bar_x = bar_empty + NSTAGES * 8;

    uint64_t pol;
    asm volatile("createpolicy.fractional.L2::evict_first.b64 %0, 1.0;" : "=l"(pol));

    if (warp == NCW) {
        if (lane == 0) {
#pragma unroll
            for (int i = 0; i < NSTAGES; i++) {
                mbar_init(bar_full + i * 8, 1);
                mbar_init(bar_empty + i * 8, NCW);
            }
            mbar_init(bar_x, 1);
            mbar_init(bar_x + 8, 1);
            asm volatile("fence.mbarrier_init.release.cluster;" ::: "memory");
            asm volatile("fence.proxy.async.shared::cta;" ::: "memory");
            mbar_expect_tx(bar_x, 128 * 4);
            mbar_expect_tx(bar_x + 8, 64 * 4);
        }
        __syncwarp();
        asm volatile("barrier.cluster.arrive.release.aligned;" ::: "memory");
        const size_t kvoff = ((size_t)(rank * NH + h) * SK + (SK - WIN)) * DH;
        const char* kb = (const char*)(p.k[br] + kvoff);
        const char* vb = (const char*)(p.v[br] + kvoff);
        const char* wob = (const char*)(p.wo[br] + (size_t)(h * DH + rank * 64) * D_MODEL);
        if (lane == 0) {
#pragma unroll
            for (int i = 0; i < NSTAGES; i++) {
                mbar_expect_tx(bar_full + i * 8, CHUNK_BYTES);
                bulk_load(sbase + SM_RING + i * CHUNK_BYTES, kb + (size_t)i * CHUNK_BYTES, CHUNK_BYTES, bar_full + i * 8, pol);
            }
        }
        __syncwarp();
        asm volatile("barrier.cluster.wait.acquire.aligned;" ::: "memory");
        if (lane == 0) {
            int s = 0;
            uint32_t ph = 0;
            for (int i = NSTAGES; i < 2 * KCHUNKS + WOCHUNKS; i++) {
                const char* src = (i < KCHUNKS) ? kb + (size_t)i * CHUNK_BYTES
                                  : (i < 2 * KCHUNKS) ? vb + (size_t)(i - KCHUNKS) * CHUNK_BYTES
                                                      : wob + (size_t)(i - 2 * KCHUNKS) * CHUNK_BYTES;
                mbar_wait(bar_empty + s * 8, ph);
                mbar_expect_tx(bar_full + s * 8, CHUNK_BYTES);
                bulk_load(sbase + SM_RING + s * CHUNK_BYTES, src, CHUNK_BYTES, bar_full + s * 8, pol);
                if (++s == NSTAGES) { s = 0; ph ^= 1; }
            }
        }
        __syncwarp();
        const int idx = cta & 63;
        uint32_t* slot = g_part + ((size_t)(br * 64 + idx) * 64) * 16 + (lane >> 2) * 16 + (lane & 3) * 4;
        uint4 v[8];
        uint32_t pending = 0xffu;
        for (int it = 0; pending; it++) {
            if (it >= SPIN_LIMIT) __trap();
#pragma unroll
            for (int i = 0; i < 8; i++) {
                if (pending & (1u << i)) {
                    asm volatile("ld.relaxed.gpu.global.v4.u32 {%0,%1,%2,%3}, [%4];"
                                 : "=r"(v[i].x), "=r"(v[i].y), "=r"(v[i].z), "=r"(v[i].w)
                                 : "l"(slot + i * 8 * 16)
                                 : "memory");
                }
            }
#pragma unroll
            for (int i = 0; i < 8; i++) {
                if (v[i].x != 0u && v[i].y != 0u && v[i].z != 0u && v[i].w != 0u) pending &= ~(1u << i);
            }
        }
        float s0 = 0.f, s1 = 0.f, s2 = 0.f, s3 = 0.f;
#pragma unroll
        for (int i = 0; i < 8; i++) {
            s0 += __uint_as_float(~v[i].x);
            s1 += __uint_as_float(~v[i].y);
            s2 += __uint_as_float(~v[i].z);
            s3 += __uint_as_float(~v[i].w);
        }
        __syncwarp();
#pragma unroll
        for (int o = 4; o < 32; o <<= 1) {
            s0 += __shfl_xor_sync(0xffffffffu, s0, o);
            s1 += __shfl_xor_sync(0xffffffffu, s1, o);
            s2 += __shfl_xor_sync(0xffffffffu, s2, o);
            s3 += __shfl_xor_sync(0xffffffffu, s3, o);
        }
        if (lane < 4) {
            uint2 o2;
            o2.x = bf16_bits(s0) | (bf16_bits(s1) << 16);
            o2.y = bf16_bits(s2) | (bf16_bits(s3) << 16);
            const int b = idx >> 5;
            __nv_bfloat16* op = p.out + b * (2 * D_MODEL) + br * D_MODEL + (idx & 31) * 16 + lane * 4;
            *reinterpret_cast<uint2*>(op) = o2;
        }
#pragma unroll
        for (int i = 0; i < 8; i++) {
            asm volatile("st.relaxed.gpu.global.v4.u32 [%0], {%1,%1,%1,%1};" ::"l"(slot + i * 8 * 16), "r"(0u) : "memory");
        }
        return;
    }

    const int g = lane >> 2;
    const int t = lane & 3;
    float* red = reinterpret_cast<float*>(smem + SM_RED);
    const uint32_t peer = rank ^ 1;

    {
        const int rg = tid >> 4, cg = tid & 15;
        const int k0 = rank * 256 + rg * 16;
        const __nv_bfloat16* wp = p.wq[br] + (size_t)k0 * (NH * DH) + h * DH + cg * 8;
        uint4 w[16];
#pragma unroll
        for (int i = 0; i < 16; i++) w[i] = ldg_stream(wp + (size_t)i * (NH * DH), pol);
        uint4 xa[2][2];
#pragma unroll
        for (int b = 0; b < 2; b++) {
            const uint4* xp = reinterpret_cast<const uint4*>(p.x[br] + b * D_MODEL + k0);
            xa[b][0] = __ldg(xp);
            xa[b][1] = __ldg(xp + 1);
        }
        asm volatile("barrier.cluster.arrive.release.aligned;" ::: "memory");
        float acc[2][8];
#pragma unroll
        for (int j = 0; j < 8; j++) { acc[0][j] = 0.f; acc[1][j] = 0.f; }
#pragma unroll
        for (int i = 0; i < 16; i++) {
            float xv[2];
#pragma unroll
            for (int b = 0; b < 2; b++) {
                const uint4 q4 = xa[b][i >> 3];
                const int wi = (i >> 1) & 3;
                const uint32_t ww = wi == 0 ? q4.x : wi == 1 ? q4.y : wi == 2 ? q4.z : q4.w;
                xv[b] = (i & 1) ? bf_hi(ww) : bf_lo(ww);
            }
            const uint32_t ws[4] = {w[i].x, w[i].y, w[i].z, w[i].w};
#pragma unroll
            for (int j = 0; j < 4; j++) {
                const float lo = bf_lo(ws[j]), hi = bf_hi(ws[j]);
                acc[0][2 * j] = fmaf(xv[0], lo, acc[0][2 * j]);
                acc[0][2 * j + 1] = fmaf(xv[0], hi, acc[0][2 * j + 1]);
                acc[1][2 * j] = fmaf(xv[1], lo, acc[1][2 * j]);
                acc[1][2 * j + 1] = fmaf(xv[1], hi, acc[1][2 * j + 1]);
            }
        }
        const bool hi16 = lane >= 16;
        float mine[8];
#pragma unroll
        for (int j = 0; j < 8; j++) {
            const float send = hi16 ? acc[0][j] : acc[1][j];
            const float keep = hi16 ? acc[1][j] : acc[0][j];
            mine[j] = keep + __shfl_xor_sync(0xffffffffu, send, 16);
        }
        float4* dst = reinterpret_cast<float4*>(red + warp * 256 + (hi16 ? 128 : 0) + cg * 8);
        dst[0] = make_float4(mine[0], mine[1], mine[2], mine[3]);
        dst[1] = make_float4(mine[4], mine[5], mine[6], mine[7]);
        asm volatile("barrier.cluster.wait.acquire.aligned;" ::: "memory");
        consumer_bar();
        float s = 0.f;
#pragma unroll
        for (int ww = 0; ww < NCW; ww++) s += red[ww * 256 + tid];
        const int b = tid >> 7, col = tid & 127;
        if (b != rank) {
            st_async_f32(mapa(sbase + SM_QX + col * 4, peer), s, mapa(bar_x, peer));
        } else {
            mbar_wait_cluster(bar_x, 0);
            const float other = reinterpret_cast<const float*>(smem + SM_QX)[col];
            reinterpret_cast<__nv_bfloat16*>(smem + SM_QS)[col] = __float2bfloat16_rn(s + other);
        }
        consumer_bar();
    }

    uint32_t koff[4];
    uint4 qf[4];
#pragma unroll
    for (int j = 0; j < 4; j++) {
        koff[j] = (uint32_t)((4 * (j ^ (g & 1)) + t) * 16);
        qf[j] = lds128(sbase + SM_QS + koff[j]);
    }

    float sc[KCHUNKS][2];
    const float scale = 0.08838834764831845f;
    {
        const uint32_t rowoff = (uint32_t)((warp * 16 + g) * ROW_BYTES);
#pragma unroll
        for (int c = 0; c < KCHUNKS; c++) {
            const int s = c % NSTAGES;
            const uint32_t ph = (c / NSTAGES) & 1;
            mbar_wait(bar_full + s * 8, ph);
            const uint32_t base = sbase + SM_RING + s * CHUNK_BYTES + rowoff;
            uint4 lo[4], hi[4];
#pragma unroll
            for (int j = 0; j < 4; j++) {
                lo[j] = lds128(base + koff[j]);
                hi[j] = lds128(base + 8 * ROW_BYTES + koff[j]);
            }
            float a0[4] = {0.f, 0.f, 0.f, 0.f}, a1[4] = {0.f, 0.f, 0.f, 0.f};
#pragma unroll
            for (int j = 0; j < 4; j++) {
                mma_bf16(a0, lo[j].x, hi[j].x, lo[j].y, hi[j].y, qf[j].x, qf[j].y);
                mma_bf16(a1, lo[j].z, hi[j].z, lo[j].w, hi[j].w, qf[j].z, qf[j].w);
            }
            __syncwarp();
            if (lane == 0) mbar_arrive(bar_empty + s * 8);
            const float r0 = (g & 1) ? (a0[1] + a1[1]) : (a0[0] + a1[0]);
            const float r1 = (g & 1) ? (a0[3] + a1[3]) : (a0[2] + a1[2]);
            sc[c][0] = bf16_round(bf16_round(r0) * scale);
            sc[c][1] = bf16_round(bf16_round(r1) * scale);
        }
    }

    uint32_t pb[KCHUNKS][2];
    {
        float* wmax = reinterpret_cast<float*>(smem + SM_WMAX);
        float* wsum = reinterpret_cast<float*>(smem + SM_WSUM);
        float m = sc[0][0];
#pragma unroll
        for (int c = 0; c < KCHUNKS; c++) m = fmaxf(m, fmaxf(sc[c][0], sc[c][1]));
#pragma unroll
        for (int o = 4; o < 32; o <<= 1) m = fmaxf(m, __shfl_xor_sync(0xffffffffu, m, o));
        if (lane == 0) wmax[warp] = m;
        consumer_bar();
#pragma unroll
        for (int ww = 0; ww < NCW; ww++) m = fmaxf(m, wmax[ww]);
        const float LOG2E = 1.4426950408889634f;
        float sum = 0.f;
#pragma unroll
        for (int c = 0; c < KCHUNKS; c++) {
            sc[c][0] = exp2f((sc[c][0] - m) * LOG2E);
            sc[c][1] = exp2f((sc[c][1] - m) * LOG2E);
            sum += sc[c][0] + sc[c][1];
        }
#pragma unroll
        for (int o = 4; o < 32; o <<= 1) sum += __shfl_xor_sync(0xffffffffu, sum, o);
        if (lane == 0) wsum[warp] = sum;
        consumer_bar();
        float tot = 0.f;
#pragma unroll
        for (int ww = 0; ww < NCW; ww++) tot += wsum[ww];
        const float inv = 1.0f / tot;
        const bool holder = (t == (g >> 1));
        const int sh = (g & 1) * 16;
#pragma unroll
        for (int c = 0; c < KCHUNKS; c++) {
            pb[c][0] = holder ? (bf16_bits(sc[c][0] * inv) << sh) : 0u;
            pb[c][1] = holder ? (bf16_bits(sc[c][1] * inv) << sh) : 0u;
        }
    }

    float acc[8][4];
#pragma unroll
    for (int i = 0; i < 8; i++) { acc[i][0] = 0.f; acc[i][1] = 0.f; acc[i][2] = 0.f; acc[i][3] = 0.f; }
    {
        const int mi = lane >> 3, r = lane & 7;
        const uint32_t rowoff = (uint32_t)((warp * 16 + r + 8 * (mi >> 1)) * ROW_BYTES + (mi & 1) * 128);
        uint32_t voff[8];
#pragma unroll
        for (int i = 0; i < 8; i++) voff[i] = rowoff + (uint32_t)((i ^ r) * 16);
#pragma unroll
        for (int c = 0; c < KCHUNKS; c++) {
            const int cc = KCHUNKS + c;
            const int s = cc % NSTAGES;
            const uint32_t ph = (cc / NSTAGES) & 1;
            mbar_wait(bar_full + s * 8, ph);
            const uint32_t base = sbase + SM_RING + s * CHUNK_BYTES;
            uint32_t a[8][4];
#pragma unroll
            for (int i = 0; i < 8; i++) ldsm_x4_trans(base + voff[i], a[i][0], a[i][1], a[i][2], a[i][3]);
#pragma unroll
            for (int i = 0; i < 8; i++) mma_bf16(acc[i], a[i][0], a[i][1], a[i][2], a[i][3], pb[c][0], pb[c][1]);
            __syncwarp();
            if (lane == 0) mbar_arrive(bar_empty + s * 8);
        }
    }
    {
#pragma unroll
        for (int hf = 0; hf < 2; hf++) {
            float u[8];
#pragma unroll
            for (int i = 0; i < 8; i++) u[i] = acc[i][2 * hf] + acc[i ^ 1][2 * hf + 1];
            float u2[4];
            u2[0] = u[0] + __shfl_xor_sync(0xffffffffu, u[2], 1);
            u2[1] = u[1] + __shfl_xor_sync(0xffffffffu, u[3], 1);
            u2[2] = u[4] + __shfl_xor_sync(0xffffffffu, u[6], 1);
            u2[3] = u[5] + __shfl_xor_sync(0xffffffffu, u[7], 1);
            const float f0 = u2[0] + __shfl_xor_sync(0xffffffffu, u2[2], 2);
            const float f1 = u2[1] + __shfl_xor_sync(0xffffffffu, u2[3], 2);
            red[warp * 128 + hf * 64 + (2 * t) * 8 + g] = f0;
            red[warp * 128 + hf * 64 + (2 * t + 1) * 8 + g] = f1;
        }
        consumer_bar();
        float* ox = reinterpret_cast<float*>(smem + SM_OX);
        if (tid < 128) {
            float s = 0.f;
#pragma unroll
            for (int ww = 0; ww < NCW; ww++) s += red[ww * 128 + tid];
            s = bf16_round(s);
            if ((tid >> 6) == rank) {
                ox[rank * 64 + (tid & 63)] = s;
            } else {
                st_async_f32(mapa(sbase + SM_OX + (rank * 64 + (tid & 63)) * 4, peer), s, mapa(bar_x + 8, peer));
            }
        }
        mbar_wait_cluster(bar_x + 8, 0);
        consumer_bar();
    }

    {
        float o00 = 0.f, o01 = 0.f, o10 = 0.f, o11 = 0.f;
#pragma unroll
        for (int c = 0; c < WOCHUNKS; c++) {
            const int cc = 2 * KCHUNKS + c;
            const int s = cc % NSTAGES;
            const uint32_t ph = (cc / NSTAGES) & 1;
            mbar_wait(bar_full + s * 8, ph);
            const uint32_t base = sbase + SM_RING + s * CHUNK_BYTES + tid * 4;
#pragma unroll
            for (int r4 = 0; r4 < WO_ROWS_PER_CHUNK / 4; r4++) {
                const uint4 xa = lds128(sbase + SM_OX + (c * WO_ROWS_PER_CHUNK + r4 * 4) * 4);
                const uint4 xb = lds128(sbase + SM_OX + (64 + c * WO_ROWS_PER_CHUNK + r4 * 4) * 4);
                const uint32_t xas[4] = {xa.x, xa.y, xa.z, xa.w};
                const uint32_t xbs[4] = {xb.x, xb.y, xb.z, xb.w};
#pragma unroll
                for (int r = 0; r < 4; r++) {
                    const uint32_t w2 = lds32(base + (r4 * 4 + r) * (D_MODEL * 2));
                    const float lo = bf_lo(w2), hi = bf_hi(w2);
                    const float fa = __uint_as_float(xas[r]), fb = __uint_as_float(xbs[r]);
                    o00 = fmaf(fa, lo, o00);
                    o01 = fmaf(fa, hi, o01);
                    o10 = fmaf(fb, lo, o10);
                    o11 = fmaf(fb, hi, o11);
                }
            }
        }
        const int contrib = cta & 63;
        uint32_t* d0 = g_part + ((size_t)(br * 64 + (tid >> 3)) * 64 + contrib) * 16 + (tid & 7) * 2;
        uint32_t* d1 = d0 + (size_t)32 * 64 * 16;
        asm volatile("st.relaxed.gpu.global.v2.u32 [%0], {%1,%2};" ::"l"(d0), "r"(enc(o00)), "r"(enc(o01)) : "memory");
        asm volatile("st.relaxed.gpu.global.v2.u32 [%0], {%1,%2};" ::"l"(d1), "r"(enc(o10)), "r"(enc(o11)) : "memory");
    }
}

}

extern "C" void kernel_launch(void* const* d_in, const int* in_sizes, int n_in, void* d_out, int out_size) {
    (void)in_sizes; (void)n_in; (void)out_size;
    static bool attr_set = false;
    if (!attr_set) {
        cudaFuncSetAttribute(fused_decode_kernel, cudaFuncAttributeMaxDynamicSharedMemorySize, SM_TOTAL);
        attr_set = true;
    }
    Params p;
    for (int i = 0; i < 2; i++) {
        p.x[i] = (const __nv_bfloat16*)d_in[5 * i + 0];
        p.k[i] = (const __nv_bfloat16*)d_in[5 * i + 1];
        p.v[i] = (const __nv_bfloat16*)d_in[5 * i + 2];
        p.wq[i] = (const __nv_bfloat16*)d_in[5 * i + 3];
        p.wo[i] = (const __nv_bfloat16*)d_in[5 * i + 4];
    }
    p.out = (__nv_bfloat16*)d_out;
    fused_decode_kernel<<<128, NTHREADS, SM_TOTAL>>>(p);
}
```

```cpp
#include <cuda_runtime.h>
#include <cuda.h>
#include <cuda_bf16.h>
#include <stdint.h>

namespace {

constexpr int D_MODEL = 512;
constexpr int NH = 32;
constexpr int SK = 8192;
constexpr int DH = 128;
constexpr int WIN = 2048;
constexpr int ROW_BYTES = DH * 2;
constexpr int CHUNK_BYTES = 32768;
constexpr int NSTAGES = 6;
#define CFG_EARLY 4
#define CFG_HINT 2
#define CFG_WOLAG 2
#define CFG_PROMO CU_TENSOR_MAP_L2_PROMOTION_L2_256B
#define CFG_HSLEEP 0
#define CFG_OWN 1
#define CFG_REPL 1
#define CFG_POLL 0
constexpr int EARLY_STAGES = CFG_EARLY;
constexpr int KCHUNKS = WIN * ROW_BYTES / CHUNK_BYTES;
constexpr int WO_BYTES = 64 * D_MODEL * 2;
constexpr int WOCHUNKS = WO_BYTES / CHUNK_BYTES;
constexpr int WO_ROWS_PER_CHUNK = CHUNK_BYTES / (D_MODEL * 2);
constexpr int NCW = 8;
constexpr int NCT = NCW * 32;
constexpr int NTHREADS = NCT + 32;

constexpr int SM_RING = 0;
constexpr int SM_RED = NSTAGES * CHUNK_BYTES;
constexpr int SM_QX = SM_RED + NCW * 256 * 4;
constexpr int SM_QS = SM_QX + 128 * 4;
constexpr int SM_OX = SM_QS + 128 * 2;
constexpr int SM_WMAX = SM_OX + 128 * 4;
constexpr int SM_WSUM = SM_WMAX + 32;
constexpr int SM_BARS = SM_WSUM + 32;
constexpr int SM_TOTAL = SM_BARS + (2 * NSTAGES + 2) * 8;

struct Params {
    alignas(64) CUtensorMap wo_map[2];
    const __nv_bfloat16* x[2];
    const __nv_bfloat16* k[2];
    const __nv_bfloat16* v[2];
    const __nv_bfloat16* wq[2];
    const __nv_bfloat16* wo[2];
    __nv_bfloat16* out;
};

__device__ uint32_t g_part[2 * 64 * 64 * 16];

constexpr int HINT_STRIDE = 64;
__device__ uint32_t g_hint[2 * NCW * HINT_STRIDE];
__device__ uint32_t g_init[2 * HINT_STRIDE];

#define TS(i)

__device__ __forceinline__ uint32_t smem_u32(const void* p) { return (uint32_t)__cvta_generic_to_shared(p); }
__device__ __forceinline__ void mbar_init(uint32_t bar, uint32_t cnt) {
    asm volatile("mbarrier.init.shared::cta.b64 [%0], %1;" ::"r"(bar), "r"(cnt) : "memory");
}
__device__ __forceinline__ void mbar_expect_tx(uint32_t bar, uint32_t bytes) {
    asm volatile("mbarrier.arrive.expect_tx.shared::cta.b64 _, [%0], %1;" ::"r"(bar), "r"(bytes) : "memory");
}
__device__ __forceinline__ void mbar_arrive(uint32_t bar) {
    asm volatile("mbarrier.arrive.shared::cta.b64 _, [%0];" ::"r"(bar) : "memory");
}
constexpr int SPIN_LIMIT = 1 << 22;
__device__ __forceinline__ bool mbar_try(uint32_t bar, uint32_t parity) {
    uint32_t ok;
    asm volatile(
        "{\n"
        ".reg .pred p;\n"
        "mbarrier.try_wait.parity.shared::cta.b64 p, [%1], %2;\n"
        "selp.u32 %0, 1, 0, p;\n"
        "}\n"
        : "=r"(ok)
        : "r"(bar), "r"(parity)
        : "memory");
    return ok != 0;
}
__device__ __forceinline__ bool mbar_try_cluster(uint32_t bar, uint32_t parity) {
    uint32_t ok;
    asm volatile(
        "{\n"
        ".reg .pred p;\n"
        "mbarrier.try_wait.parity.acquire.cluster.shared::cta.b64 p, [%1], %2;\n"
        "selp.u32 %0, 1, 0, p;\n"
        "}\n"
        : "=r"(ok)
        : "r"(bar), "r"(parity)
        : "memory");
    return ok != 0;
}
__device__ __forceinline__ void mbar_wait(uint32_t bar, uint32_t parity) {
    if (mbar_try(bar, parity)) return;
#pragma unroll 1
    for (int i = 0; i < SPIN_LIMIT; i++)
        if (mbar_try(bar, parity)) return;
    __trap();
}
__device__ __forceinline__ void mbar_wait_cluster(uint32_t bar, uint32_t parity) {
#pragma unroll 1
    for (int i = 0; i < SPIN_LIMIT; i++)
        if (mbar_try_cluster(bar, parity)) return;
    __trap();
}
__device__ __forceinline__ void bulk_load(uint32_t dst, const void* src, uint32_t bytes, uint32_t bar, uint64_t pol) {
    asm volatile(
        "cp.async.bulk.shared::cluster.global.mbarrier::complete_tx::bytes.L2::cache_hint [%0], [%1], %2, [%3], %4;" ::"r"(dst),
        "l"(src), "r"(bytes), "r"(bar), "l"(pol)
        : "memory");
}
__device__ __forceinline__ uint32_t mapa(uint32_t addr, uint32_t rank) {
    uint32_t r;
    asm volatile("mapa.shared::cluster.u32 %0, %1, %2;" : "=r"(r) : "r"(addr), "r"(rank));
    return r;
}
__device__ __forceinline__ void st_async_f32(uint32_t raddr, float v, uint32_t rbar) {
    asm volatile("st.async.shared::cluster.mbarrier::complete_tx::bytes.f32 [%0], %1, [%2];" ::"r"(raddr), "f"(v), "r"(rbar)
                 : "memory");
}
__device__ __forceinline__ void st_async_u32(uint32_t raddr, uint32_t v, uint32_t rbar) {
    asm volatile("st.async.shared::cluster.mbarrier::complete_tx::bytes.u32 [%0], %1, [%2];" ::"r"(raddr), "r"(v), "r"(rbar)
                 : "memory");
}
__device__ __forceinline__ void consumer_bar() { asm volatile("bar.sync 1, %0;" ::"n"(NCT) : "memory"); }
__device__ __forceinline__ uint4 lds128(uint32_t a) {
    uint4 v;
    asm volatile("ld.shared.v4.u32 {%0,%1,%2,%3}, [%4];" : "=r"(v.x), "=r"(v.y), "=r"(v.z), "=r"(v.w) : "r"(a));
    return v;
}
__device__ __forceinline__ uint32_t lds32(uint32_t a) {
    uint32_t v;
    asm volatile("ld.shared.u32 %0, [%1];" : "=r"(v) : "r"(a));
    return v;
}
__device__ __forceinline__ void ldsm_x4_trans(uint32_t a, uint32_t& r0, uint32_t& r1, uint32_t& r2, uint32_t& r3) {
    asm volatile("ldmatrix.sync.aligned.m8n8.x4.trans.shared.b16 {%0,%1,%2,%3}, [%4];"
                 : "=r"(r0), "=r"(r1), "=r"(r2), "=r"(r3)
                 : "r"(a));
}
__device__ __forceinline__ void mma_bf16(float (&c)[4], uint32_t a0, uint32_t a1, uint32_t a2, uint32_t a3, uint32_t b0,
                                         uint32_t b1) {
    asm("mma.sync.aligned.m16n8k16.row.col.f32.bf16.bf16.f32 {%0,%1,%2,%3}, {%4,%5,%6,%7}, {%8,%9}, {%0,%1,%2,%3};"
        : "+f"(c[0]), "+f"(c[1]), "+f"(c[2]), "+f"(c[3])
        : "r"(a0), "r"(a1), "r"(a2), "r"(a3), "r"(b0), "r"(b1));
}
__device__ __forceinline__ uint4 ldg_stream(const void* p, uint64_t pol) {
    uint4 v;
    asm volatile("ld.global.nc.L1::no_allocate.L2::cache_hint.v4.u32 {%0,%1,%2,%3}, [%4], %5;"
                 : "=r"(v.x), "=r"(v.y), "=r"(v.z), "=r"(v.w)
                 : "l"(p), "l"(pol));
    return v;
}
__device__ __forceinline__ float bf_lo(uint32_t w) { return __uint_as_float(w << 16); }
__device__ __forceinline__ float bf_hi(uint32_t w) { return __uint_as_float(w & 0xffff0000u); }
__device__ __forceinline__ float bf16_round(float v) { return __bfloat162float(__float2bfloat16_rn(v)); }
__device__ __forceinline__ uint32_t bf16_bits(float v) { return (uint32_t)__bfloat16_as_ushort(__float2bfloat16_rn(v)); }
__device__ __forceinline__ uint32_t enc(float v) {
    uint32_t b = __float_as_uint(v);
    if (b == 0xffffffffu) b = 0x7fffffffu;
    return ~b;
}

__global__ void __cluster_dims__(2, 1, 1) __launch_bounds__(NTHREADS, 1) fused_decode_kernel(const __grid_constant__ Params p) {
    extern __shared__ __align__(1024) unsigned char smem[];
    const uint32_t sbase = smem_u32(smem);
    const int cta = blockIdx.x;
    const int rank = cta & 1;
    const int pair = cta >> 1;
    const int br = pair >> 5;
    const int h = pair & 31;
    const int tid = threadIdx.x;
    const int warp = tid >> 5;
    const int lane = tid & 31;
    const uint32_t bar_full = sbase + SM_BARS;
    const uint32_t bar_empty = bar_full + NSTAGES * 8;
    const uint32_t bar_x = bar_empty + NSTAGES * 8;

    uint64_t pol;
    asm volatile("createpolicy.fractional.L2::evict_first.b64 %0, 1.0;" : "=l"(pol));

    if (warp == 0) TS(0);
    if (warp == NCW) {
        if (lane == 0) {
#pragma unroll
            for (int i = 0; i < NSTAGES; i++) {
                mbar_init(bar_full + i * 8, 1);
                mbar_init(bar_empty + i * 8, NCW);
            }
            mbar_init(bar_x, 1);
            mbar_init(bar_x + 8, 1);
            asm volatile("fence.mbarrier_init.release.cluster;" ::: "memory");
            asm volatile("fence.proxy.async.shared::cta;" ::: "memory");
            mbar_expect_tx(bar_x, 128 * 4);
            mbar_expect_tx(bar_x + 8, 64 * 4);
        }
        const size_t kvoff = ((size_t)(rank * NH + h) * SK + (SK - WIN)) * DH;
        const char* kb = (const char*)(p.k[br] + kvoff);
        const char* vb = (const char*)(p.v[br] + kvoff);
        if (lane == 0) {
#pragma unroll
            for (int i = 0; i < EARLY_STAGES; i++) {
                mbar_expect_tx(bar_full + i * 8, CHUNK_BYTES);
                bulk_load(sbase + SM_RING + i * CHUNK_BYTES, kb + (size_t)i * CHUNK_BYTES, CHUNK_BYTES, bar_full + i * 8, pol);
            }
        }
        __syncwarp();
        asm volatile("barrier.cluster.arrive.relaxed.aligned;" ::: "memory");
        asm volatile("barrier.cluster.wait.acquire.aligned;" ::: "memory");
        const uint32_t* hint_ptr = g_hint + (br * NCW + (cta & (CFG_REPL - 1))) * HINT_STRIDE;
        uint32_t hint_base;
        asm volatile("ld.relaxed.gpu.global.u32 %0, [%1];" : "=r"(hint_base) : "l"(hint_ptr) : "memory");
        hint_base &= ~63u;
        if (lane == 0) asm volatile("prefetch.tensormap [%0];" ::"l"(&p.wo_map[br]) : "memory");
        const int idx = cta & 63;
        uint32_t* slot = g_part + ((size_t)(br * 64 + idx) * 64) * 16 + (lane >> 2) * 16 + (lane & 3) * 4;
        uint32_t* init_ptr = g_init + br * HINT_STRIDE;
        uint32_t init_base;
        asm volatile("ld.relaxed.gpu.global.u32 %0, [%1];" : "=r"(init_base) : "l"(init_ptr) : "memory");
        init_base &= ~63u;
#pragma unroll
        for (int i = 0; i < 8; i++)
            asm volatile("st.relaxed.gpu.global.v4.u32 [%0], {%1,%1,%1,%1};" ::"l"(slot + i * 8 * 16), "r"(0u) : "memory");
        __syncwarp();
        if (lane == 0) {
            asm volatile("fence.acq_rel.gpu;" ::: "memory");
            asm volatile("red.relaxed.gpu.global.add.u32 [%0], 1;" ::"l"(init_ptr) : "memory");
        }
        asm volatile("bar.sync 2, %0;" ::"n"(NTHREADS) : "memory");
        if (lane == 0) {
#pragma unroll
            for (int i = EARLY_STAGES; i < NSTAGES; i++) {
                mbar_expect_tx(bar_full + i * 8, CHUNK_BYTES);
                bulk_load(sbase + SM_RING + i * CHUNK_BYTES, kb + (size_t)i * CHUNK_BYTES, CHUNK_BYTES, bar_full + i * 8, pol);
            }
        }
        if (lane == 0) {
            for (int it = 0;; it++) {
                if (it >= SPIN_LIMIT) __trap();
                uint32_t c;
                asm volatile("ld.acquire.gpu.global.u32 %0, [%1];" : "=r"(c) : "l"(init_ptr) : "memory");
                if (c - init_base >= 64u) break;
            }
            int s = 0;
            uint32_t ph = 0;
            for (int i = NSTAGES; i < 2 * KCHUNKS + WOCHUNKS; i++) {
                const char* src = (i < KCHUNKS) ? kb + (size_t)i * CHUNK_BYTES : vb + (size_t)(i - KCHUNKS) * CHUNK_BYTES;
                mbar_wait(bar_empty + s * 8, ph);
                if (i >= 2 * KCHUNKS) {
                    const int n = i - NSTAGES + CFG_WOLAG;
                    mbar_wait(bar_empty + (n % NSTAGES) * 8, (n / NSTAGES) & 1);
                }
                mbar_expect_tx(bar_full + s * 8, CHUNK_BYTES);
                if (i < 2 * KCHUNKS) {
                    bulk_load(sbase + SM_RING + s * CHUNK_BYTES, src, CHUNK_BYTES, bar_full + s * 8, pol);
                } else {
#pragma unroll
                    for (int w = 0; w < 4; w++) {
                        asm volatile(
                            "cp.async.bulk.tensor.2d.shared::cluster.global.tile.mbarrier::complete_tx::bytes.L2::cache_hint "
                            "[%0], [%1, {%2, %3}], [%4], %5;" ::"r"(sbase + SM_RING + s * CHUNK_BYTES + w * 8192),
                            "l"(&p.wo_map[br]), "r"(((i - 2 * KCHUNKS) * 4 + w) * 64), "r"(h * DH + rank * 64),
                            "r"(bar_full + s * 8), "l"(pol)
                            : "memory");
                    }
                }
                if (++s == NSTAGES) { s = 0; ph ^= 1; }
            }
        }
        __syncwarp();
        asm volatile("bar.sync 3, %0;" ::"n"(NTHREADS) : "memory");
        if (CFG_HINT < 64 && lane == 0) {
            for (int it = 0;; it++) {
                if (it >= SPIN_LIMIT) __trap();
                uint32_t c;
                asm volatile("ld.relaxed.gpu.global.u32 %0, [%1];" : "=r"(c) : "l"(hint_ptr) : "memory");
                if (c - hint_base >= (uint32_t)(64 - CFG_HINT)) break;
            }
        }
        __syncwarp();
        TS(8);
        uint4 v[8];
        uint32_t pending = 0xffu;
        for (int it = 0; pending; it++) {
            if (it >= SPIN_LIMIT) __trap();
#pragma unroll
            for (int i = 0; i < 8; i++) {
                if (pending & (1u << i)) {
                    asm volatile("ld.relaxed.gpu.global.v4.u32 {%0,%1,%2,%3}, [%4];"
                                 : "=r"(v[i].x), "=r"(v[i].y), "=r"(v[i].z), "=r"(v[i].w)
                                 : "l"(slot + i * 8 * 16)
                                 : "memory");
                }
            }
#pragma unroll
            for (int i = 0; i < 8; i++) {
                if (v[i].x != 0u && v[i].y != 0u && v[i].z != 0u && v[i].w != 0u) pending &= ~(1u << i);
            }
        }
        TS(9);
        float s0 = 0.f, s1 = 0.f, s2 = 0.f, s3 = 0.f;
#pragma unroll
        for (int i = 0; i < 8; i++) {
            s0 += __uint_as_float(~v[i].x);
            s1 += __uint_as_float(~v[i].y);
            s2 += __uint_as_float(~v[i].z);
            s3 += __uint_as_float(~v[i].w);
        }
        __syncwarp();
#pragma unroll
        for (int o = 4; o < 32; o <<= 1) {
            s0 += __shfl_xor_sync(0xffffffffu, s0, o);
            s1 += __shfl_xor_sync(0xffffffffu, s1, o);
            s2 += __shfl_xor_sync(0xffffffffu, s2, o);
            s3 += __shfl_xor_sync(0xffffffffu, s3, o);
        }
        if (lane < 8) {
            const int b = idx >> 5;
            const uint32_t w = (lane < 4) ? (bf16_bits(s0) | (bf16_bits(s2) << 16)) : (bf16_bits(s1) | (bf16_bits(s3) << 16));
            __nv_bfloat16* op = p.out + b * (2 * D_MODEL) + br * D_MODEL + (idx & 31) * 16 + lane * 2;
            *reinterpret_cast<uint32_t*>(op) = w;
        }
        return;
    }

    const int g = lane >> 2;
    const int t = lane & 3;
    float* red = reinterpret_cast<float*>(smem + SM_RED);
    const uint32_t peer = rank ^ 1;

    {
        const int rg = tid >> 4, cg = tid & 15;
        const int k0 = rank * 256 + rg * 16;
        const __nv_bfloat16* wp = p.wq[br] + (size_t)k0 * (NH * DH) + h * DH + cg * 8;
        uint4 w[16];
#pragma unroll
        for (int i = 0; i < 16; i++) w[i] = ldg_stream(wp + (size_t)i * (NH * DH), pol);
        uint4 xa[2][2];
#pragma unroll
        for (int b = 0; b < 2; b++) {
            const uint4* xp = reinterpret_cast<const uint4*>(p.x[br] + b * D_MODEL + k0);
            xa[b][0] = __ldg(xp);
            xa[b][1] = __ldg(xp + 1);
        }
        asm volatile("barrier.cluster.arrive.relaxed.aligned;" ::: "memory");
        float acc[2][8];
#pragma unroll
        for (int j = 0; j < 8; j++) { acc[0][j] = 0.f; acc[1][j] = 0.f; }
#pragma unroll
        for (int i = 0; i < 16; i++) {
            float xv[2];
#pragma unroll
            for (int b = 0; b < 2; b++) {
                const uint4 q4 = xa[b][i >> 3];
                const int wi = (i >> 1) & 3;
                const uint32_t ww = wi == 0 ? q4.x : wi == 1 ? q4.y : wi == 2 ? q4.z : q4.w;
                xv[b] = (i & 1) ? bf_hi(ww) : bf_lo(ww);
            }
            const uint32_t ws[4] = {w[i].x, w[i].y, w[i].z, w[i].w};
#pragma unroll
            for (int j = 0; j < 4; j++) {
                const float lo = bf_lo(ws[j]), hi = bf_hi(ws[j]);
                acc[0][2 * j] = fmaf(xv[0], lo, acc[0][2 * j]);
                acc[0][2 * j + 1] = fmaf(xv[0], hi, acc[0][2 * j + 1]);
                acc[1][2 * j] = fmaf(xv[1], lo, acc[1][2 * j]);
                acc[1][2 * j + 1] = fmaf(xv[1], hi, acc[1][2 * j + 1]);
            }
        }
        asm volatile("bar.arrive 2, %0;" ::"n"(NTHREADS) : "memory");
        const bool hi16 = lane >= 16;
        float mine[8];
#pragma unroll
        for (int j = 0; j < 8; j++) {
            const float send = hi16 ? acc[0][j] : acc[1][j];
            const float keep = hi16 ? acc[1][j] : acc[0][j];
            mine[j] = keep + __shfl_xor_sync(0xffffffffu, send, 16);
        }
        float4* dst = reinterpret_cast<float4*>(red + warp * 256 + (hi16 ? 128 : 0) + cg * 8);
        dst[0] = make_float4(mine[0], mine[1], mine[2], mine[3]);
        dst[1] = make_float4(mine[4], mine[5], mine[6], mine[7]);
        TS(1);
        asm volatile("barrier.cluster.wait.acquire.aligned;" ::: "memory");
        consumer_bar();
        float s = 0.f;
#pragma unroll
        for (int ww = 0; ww < NCW; ww++) s += red[ww * 256 + tid];
        const int b = tid >> 7, col = tid & 127;
        if (b != rank) {
            st_async_f32(mapa(sbase + SM_QX + col * 4, peer), s, mapa(bar_x, peer));
        } else {
            mbar_wait_cluster(bar_x, 0);
            const float other = reinterpret_cast<const float*>(smem + SM_QX)[col];
            reinterpret_cast<__nv_bfloat16*>(smem + SM_QS)[col] = __float2bfloat16_rn(s + other);
        }
        consumer_bar();
    }

    TS(2);
    uint32_t koff[4];
    uint4 qf[4];
#pragma unroll
    for (int j = 0; j < 4; j++) {
        koff[j] = (uint32_t)((4 * (j ^ (g & 1)) + t) * 16);
        qf[j] = lds128(sbase + SM_QS + koff[j]);
    }

    float sc[KCHUNKS][2];
    const float scale = 0.08838834764831845f;
    {
        const uint32_t rowoff = (uint32_t)((warp * 16 + g) * ROW_BYTES);
#pragma unroll
        for (int c = 0; c < KCHUNKS; c++) {
            const int s = c % NSTAGES;
            const uint32_t ph = (c / NSTAGES) & 1;
            mbar_wait(bar_full + s * 8, ph);
            const uint32_t base = sbase + SM_RING + s * CHUNK_BYTES + rowoff;
            uint4 lo[4], hi[4];
#pragma unroll
            for (int j = 0; j < 4; j++) {
                lo[j] = lds128(base + koff[j]);
                hi[j] = lds128(base + 8 * ROW_BYTES + koff[j]);
            }
            float a0[4] = {0.f, 0.f, 0.f, 0.f}, a1[4] = {0.f, 0.f, 0.f, 0.f};
#pragma unroll
            for (int j = 0; j < 4; j++) {
                mma_bf16(a0, lo[j].x, hi[j].x, lo[j].y, hi[j].y, qf[j].x, qf[j].y);
                mma_bf16(a1, lo[j].z, hi[j].z, lo[j].w, hi[j].w, qf[j].z, qf[j].w);
            }
            __syncwarp();
            if (lane == 0) mbar_arrive(bar_empty + s * 8);
            const float r0 = (g & 1) ? (a0[1] + a1[1]) : (a0[0] + a1[0]);
            const float r1 = (g & 1) ? (a0[3] + a1[3]) : (a0[2] + a1[2]);
            sc[c][0] = bf16_round(bf16_round(r0) * scale);
            sc[c][1] = bf16_round(bf16_round(r1) * scale);
        }
    }

    TS(3);
    uint32_t pb[KCHUNKS][2];
    {
        float* wmax = reinterpret_cast<float*>(smem + SM_WMAX);
        float* wsum = reinterpret_cast<float*>(smem + SM_WSUM);
        float m = sc[0][0];
#pragma unroll
        for (int c = 0; c < KCHUNKS; c++) m = fmaxf(m, fmaxf(sc[c][0], sc[c][1]));
#pragma unroll
        for (int o = 4; o < 32; o <<= 1) m = fmaxf(m, __shfl_xor_sync(0xffffffffu, m, o));
        if (lane == 0) wmax[warp] = m;
        consumer_bar();
#pragma unroll
        for (int ww = 0; ww < NCW; ww++) m = fmaxf(m, wmax[ww]);
        const float LOG2E = 1.4426950408889634f;
        float sum = 0.f;
#pragma unroll
        for (int c = 0; c < KCHUNKS; c++) {
            sc[c][0] = exp2f((sc[c][0] - m) * LOG2E);
            sc[c][1] = exp2f((sc[c][1] - m) * LOG2E);
            sum += sc[c][0] + sc[c][1];
        }
#pragma unroll
        for (int o = 4; o < 32; o <<= 1) sum += __shfl_xor_sync(0xffffffffu, sum, o);
        if (lane == 0) wsum[warp] = sum;
        consumer_bar();
        float tot = 0.f;
#pragma unroll
        for (int ww = 0; ww < NCW; ww++) tot += wsum[ww];
        const float inv = 1.0f / tot;
        const bool holder = (t == (g >> 1));
        const int sh = (g & 1) * 16;
#pragma unroll
        for (int c = 0; c < KCHUNKS; c++) {
            pb[c][0] = holder ? (bf16_bits(sc[c][0] * inv) << sh) : 0u;
            pb[c][1] = holder ? (bf16_bits(sc[c][1] * inv) << sh) : 0u;
        }
    }

    TS(4);
    float acc[8][4];
#pragma unroll
    for (int i = 0; i < 8; i++) { acc[i][0] = 0.f; acc[i][1] = 0.f; acc[i][2] = 0.f; acc[i][3] = 0.f; }
    {
        const int mi = lane >> 3, r = lane & 7;
        const uint32_t rowoff = (uint32_t)((warp * 16 + r + 8 * (mi >> 1)) * ROW_BYTES + (mi & 1) * 128);
        uint32_t voff[8];
#pragma unroll
        for (int i = 0; i < 8; i++) voff[i] = rowoff + (uint32_t)((i ^ r) * 16);
#pragma unroll
        for (int c = 0; c < KCHUNKS; c++) {
            const int cc = KCHUNKS + c;
            const int s = cc % NSTAGES;
            const uint32_t ph = (cc / NSTAGES) & 1;
            mbar_wait(bar_full + s * 8, ph);
            const uint32_t base = sbase + SM_RING + s * CHUNK_BYTES;
            uint32_t a[8][4];
#pragma unroll
            for (int i = 0; i < 8; i++) ldsm_x4_trans(base + voff[i], a[i][0], a[i][1], a[i][2], a[i][3]);
#pragma unroll
            for (int i = 0; i < 8; i++) mma_bf16(acc[i], a[i][0], a[i][1], a[i][2], a[i][3], pb[c][0], pb[c][1]);
            __syncwarp();
            if (lane == 0) mbar_arrive(bar_empty + s * 8);
        }
    }
    TS(5);
    {
#pragma unroll
        for (int hf = 0; hf < 2; hf++) {
            float u[8];
#pragma unroll
            for (int i = 0; i < 8; i++) u[i] = acc[i][2 * hf] + acc[i ^ 1][2 * hf + 1];
            float u2[4];
            u2[0] = u[0] + __shfl_xor_sync(0xffffffffu, u[2], 1);
            u2[1] = u[1] + __shfl_xor_sync(0xffffffffu, u[3], 1);
            u2[2] = u[4] + __shfl_xor_sync(0xffffffffu, u[6], 1);
            u2[3] = u[5] + __shfl_xor_sync(0xffffffffu, u[7], 1);
            const float f0 = u2[0] + __shfl_xor_sync(0xffffffffu, u2[2], 2);
            const float f1 = u2[1] + __shfl_xor_sync(0xffffffffu, u2[3], 2);
            red[warp * 128 + hf * 64 + (2 * t) * 8 + g] = f0;
            red[warp * 128 + hf * 64 + (2 * t + 1) * 8 + g] = f1;
        }
        consumer_bar();
        if (tid < 128) {
            float s = 0.f;
#pragma unroll
            for (int ww = 0; ww < NCW; ww++) s += red[ww * 128 + tid];
            const uint32_t mine = bf16_bits(s);
            const uint32_t other = __shfl_down_sync(0xffffffffu, mine, 1);
            if ((tid & 1) == 0) {
                const int row = tid & 63;
                const uint32_t dst = (uint32_t)(tid >> 6);
                const uint32_t off = sbase + SM_OX + (uint32_t)((rank * 32 + ((row >> 1) & 3) * 8 + (row >> 3)) * 4);
                st_async_u32(mapa(off, dst), mine | (other << 16), mapa(bar_x + 8, dst));
            }
        }
    }

    TS(6);
    {
        const int mi = lane >> 3, r = lane & 7;
        uint32_t a[4][4][4];
        {
            constexpr int cc0 = 2 * KCHUNKS, cc1 = 2 * KCHUNKS + 1;
            const int s = (warp < 4) ? (cc0 % NSTAGES) : (cc1 % NSTAGES);
            const uint32_t ph = (warp < 4) ? ((cc0 / NSTAGES) & 1) : ((cc1 / NSTAGES) & 1);
            mbar_wait(bar_full + s * 8, ph);
            const uint32_t base = sbase + SM_RING + s * CHUNK_BYTES + (warp & 3) * 8192 + (uint32_t)((r + 8 * (mi >> 1)) * 128);
#pragma unroll
            for (int ks = 0; ks < 4; ks++)
#pragma unroll
                for (int j = 0; j < 4; j++)
                    ldsm_x4_trans(base + (uint32_t)(ks * 16 * 128) + (uint32_t)(((2 * j + (mi & 1)) ^ r) * 16), a[ks][j][0],
                                  a[ks][j][1], a[ks][j][2], a[ks][j][3]);
        }
        TS(10);
        mbar_wait_cluster(bar_x + 8, 0);
        TS(11);
        const int contrib = cta & 63;
        const uint4 o0 = lds128(sbase + SM_OX + (uint32_t)(((g & 1) * 32 + t * 8) * 4));
        const uint4 o1 = lds128(sbase + SM_OX + (uint32_t)(((g & 1) * 32 + t * 8 + 4) * 4));
        const uint32_t ob[8] = {o0.x, o0.y, o0.z, o0.w, o1.x, o1.y, o1.z, o1.w};
        float e[4][4];
#pragma unroll
        for (int ks = 0; ks < 4; ks++) { e[ks][0] = 0.f; e[ks][1] = 0.f; e[ks][2] = 0.f; e[ks][3] = 0.f; }
#pragma unroll
        for (int j = 0; j < 4; j++) {
            const bool on = (g >> 1) == j;
#pragma unroll
            for (int ks = 0; ks < 4; ks++)
                mma_bf16(e[ks], a[ks][j][0], a[ks][j][1], a[ks][j][2], a[ks][j][3], on ? ob[2 * ks] : 0u,
                         on ? ob[2 * ks + 1] : 0u);
        }
        float f[4];
#pragma unroll
        for (int x = 0; x < 4; x++) f[x] = (e[0][x] + e[1][x]) + (e[2][x] + e[3][x]);
#pragma unroll
        for (int b = 0; b < 2; b++) {
            uint32_t* d = g_part + ((size_t)(br * 64 + b * 32 + warp * 4 + t) * 64 + contrib) * 16 + g * 2;
            asm volatile("st.relaxed.gpu.global.v2.u32 [%0], {%1,%2};" ::"l"(d), "r"(enc(f[b])), "r"(enc(f[2 + b])) : "memory");
        }
        if (CFG_HINT < 64 && lane == 0 && warp < CFG_REPL)
            asm volatile("red.relaxed.gpu.global.add.u32 [%0], 1;" ::"l"(g_hint + (br * NCW + warp) * HINT_STRIDE) : "memory");
        asm volatile("bar.arrive 3, %0;" ::"n"(NTHREADS) : "memory");
        TS(7);
    }
}

}

typedef CUresult (*EncodeTiledFn)(CUtensorMap*, CUtensorMapDataType, cuuint32_t, void*, const cuuint64_t*, const cuuint64_t*,
                                  const cuuint32_t*, const cuuint32_t*, CUtensorMapInterleave, CUtensorMapSwizzle,
                                  CUtensorMapL2promotion, CUtensorMapFloatOOBfill);

extern "C" void kernel_launch(void* const* d_in, const int* in_sizes, int n_in, void* d_out, int out_size) {
    (void)in_sizes; (void)n_in; (void)out_size;
    static EncodeTiledFn encode = nullptr;
    if (!encode) {
        cudaFuncSetAttribute(fused_decode_kernel, cudaFuncAttributeMaxDynamicSharedMemorySize, SM_TOTAL);
        void* fn = nullptr;
        cudaDriverEntryPointQueryResult qres;
        cudaGetDriverEntryPoint("cuTensorMapEncodeTiled", &fn, cudaEnableDefault, &qres);
        encode = (EncodeTiledFn)fn;
    }
    Params p;
    for (int i = 0; i < 2; i++) {
        p.x[i] = (const __nv_bfloat16*)d_in[5 * i + 0];
        p.k[i] = (const __nv_bfloat16*)d_in[5 * i + 1];
        p.v[i] = (const __nv_bfloat16*)d_in[5 * i + 2];
        p.wq[i] = (const __nv_bfloat16*)d_in[5 * i + 3];
        p.wo[i] = (const __nv_bfloat16*)d_in[5 * i + 4];
        const cuuint64_t gdim[2] = {(cuuint64_t)D_MODEL, (cuuint64_t)(NH * DH)};
        const cuuint64_t gstride[1] = {(cuuint64_t)D_MODEL * 2};
        const cuuint32_t box[2] = {64u, 64u};
        const cuuint32_t estr[2] = {1u, 1u};
        encode(&p.wo_map[i], CU_TENSOR_MAP_DATA_TYPE_BFLOAT16, 2, d_in[5 * i + 4], gdim, gstride, box, estr,
               CU_TENSOR_MAP_INTERLEAVE_NONE, CU_TENSOR_MAP_SWIZZLE_128B, CFG_PROMO, CU_TENSOR_MAP_FLOAT_OOB_FILL_NONE);
    }
    p.out = (__nv_bfloat16*)d_out;
    fused_decode_kernel<<<128, NTHREADS, SM_TOTAL>>>(p);
}
```

```cpp
#include <cuda_runtime.h>
#include <cuda.h>
#include <cuda_bf16.h>
#include <stdint.h>

namespace {

constexpr int D_MODEL = 512;
constexpr int NH = 32;
constexpr int SK = 8192;
constexpr int DH = 128;
constexpr int WIN = 2048;
constexpr int ROW_BYTES = DH * 2;
constexpr int CHUNK_BYTES = 32768;
constexpr int NSTAGES = 6;
constexpr int EARLY_STAGES = 4;
constexpr int RAMP_CYCLES = 3000;
constexpr int WO_LAG = 2;
constexpr int GATE_SLACK = 2;
constexpr int KCHUNKS = WIN * ROW_BYTES / CHUNK_BYTES;
constexpr int WOCHUNKS = 2;
constexpr int NCW = 8;
constexpr int NCT = NCW * 32;
constexpr int NTHREADS = NCT + 32;
constexpr int NCTAS = 128;
constexpr int SPIN_LIMIT = 1 << 22;

constexpr int SM_RING = 0;
constexpr int SM_RED = NSTAGES * CHUNK_BYTES;
constexpr int SM_QX = SM_RED + NCW * 256 * 4;
constexpr int SM_QS = SM_QX + 128 * 4;
constexpr int SM_OX = SM_QS + 128 * 2;
constexpr int SM_WMAX = SM_OX + 64 * 4;
constexpr int SM_WSUM = SM_WMAX + 32;
constexpr int SM_BARS = SM_WSUM + 32;
constexpr int SM_TOTAL = SM_BARS + (2 * NSTAGES + 2) * 8;

struct Params {
    alignas(64) CUtensorMap wo_map[2];
    const __nv_bfloat16* x[2];
    const __nv_bfloat16* k[2];
    const __nv_bfloat16* v[2];
    const __nv_bfloat16* wq[2];
    __nv_bfloat16* out;
};

__device__ uint32_t g_part[2 * 64 * 64 * 16];
__device__ uint32_t g_ctr[2 * 128];

__device__ __forceinline__ uint32_t smem_u32(const void* p) { return (uint32_t)__cvta_generic_to_shared(p); }
__device__ __forceinline__ void mbar_init(uint32_t bar, uint32_t cnt) {
    asm volatile("mbarrier.init.shared::cta.b64 [%0], %1;" ::"r"(bar), "r"(cnt) : "memory");
}
__device__ __forceinline__ void mbar_expect_tx(uint32_t bar, uint32_t bytes) {
    asm volatile("mbarrier.arrive.expect_tx.shared::cta.b64 _, [%0], %1;" ::"r"(bar), "r"(bytes) : "memory");
}
__device__ __forceinline__ void mbar_arrive(uint32_t bar) {
    asm volatile("mbarrier.arrive.shared::cta.b64 _, [%0];" ::"r"(bar) : "memory");
}
__device__ __forceinline__ bool mbar_try(uint32_t bar, uint32_t parity) {
    uint32_t ok;
    asm volatile(
        "{\n"
        ".reg .pred p;\n"
        "mbarrier.try_wait.parity.shared::cta.b64 p, [%1], %2;\n"
        "selp.u32 %0, 1, 0, p;\n"
        "}\n"
        : "=r"(ok)
        : "r"(bar), "r"(parity)
        : "memory");
    return ok != 0;
}
__device__ __forceinline__ bool mbar_try_cluster(uint32_t bar, uint32_t parity) {
    uint32_t ok;
    asm volatile(
        "{\n"
        ".reg .pred p;\n"
        "mbarrier.try_wait.parity.acquire.cluster.shared::cta.b64 p, [%1], %2;\n"
        "selp.u32 %0, 1, 0, p;\n"
        "}\n"
        : "=r"(ok)
        : "r"(bar), "r"(parity)
        : "memory");
    return ok != 0;
}
__device__ __forceinline__ void mbar_wait(uint32_t bar, uint32_t parity) {
    if (mbar_try(bar, parity)) return;
#pragma unroll 1
    for (int i = 0; i < SPIN_LIMIT; i++)
        if (mbar_try(bar, parity)) return;
    __trap();
}
__device__ __forceinline__ void mbar_wait_cluster(uint32_t bar, uint32_t parity) {
#pragma unroll 1
    for (int i = 0; i < SPIN_LIMIT; i++)
        if (mbar_try_cluster(bar, parity)) return;
    __trap();
}
__device__ __forceinline__ void bulk_load(uint32_t dst, const void* src, uint32_t bytes, uint32_t bar, uint64_t pol) {
    asm volatile(
        "cp.async.bulk.shared::cluster.global.mbarrier::complete_tx::bytes.L2::cache_hint [%0], [%1], %2, [%3], %4;" ::"r"(dst),
        "l"(src), "r"(bytes), "r"(bar), "l"(pol)
        : "memory");
}
__device__ __forceinline__ void tensor_load_2d(uint32_t dst, const CUtensorMap* map, int c0, int c1, uint32_t bar,
                                               uint64_t pol) {
    asm volatile(
        "cp.async.bulk.tensor.2d.shared::cluster.global.tile.mbarrier::complete_tx::bytes.L2::cache_hint "
        "[%0], [%1, {%2, %3}], [%4], %5;" ::"r"(dst),
        "l"(map), "r"(c0), "r"(c1), "r"(bar), "l"(pol)
        : "memory");
}
__device__ __forceinline__ uint32_t mapa(uint32_t addr, uint32_t rank) {
    uint32_t r;
    asm volatile("mapa.shared::cluster.u32 %0, %1, %2;" : "=r"(r) : "r"(addr), "r"(rank));
    return r;
}
__device__ __forceinline__ void st_async_u32(uint32_t raddr, uint32_t v, uint32_t rbar) {
    asm volatile("st.async.shared::cluster.mbarrier::complete_tx::bytes.u32 [%0], %1, [%2];" ::"r"(raddr), "r"(v), "r"(rbar)
                 : "memory");
}
__device__ __forceinline__ void consumer_bar() { asm volatile("bar.sync 1, %0;" ::"n"(NCT) : "memory"); }
__device__ __forceinline__ uint4 lds128(uint32_t a) {
    uint4 v;
    asm volatile("ld.shared.v4.u32 {%0,%1,%2,%3}, [%4];" : "=r"(v.x), "=r"(v.y), "=r"(v.z), "=r"(v.w) : "r"(a));
    return v;
}
__device__ __forceinline__ void ldsm_x4_trans(uint32_t a, uint32_t (&r)[4]) {
    asm volatile("ldmatrix.sync.aligned.m8n8.x4.trans.shared.b16 {%0,%1,%2,%3}, [%4];"
                 : "=r"(r[0]), "=r"(r[1]), "=r"(r[2]), "=r"(r[3])
                 : "r"(a));
}
__device__ __forceinline__ void mma_bf16(float (&c)[4], uint32_t a0, uint32_t a1, uint32_t a2, uint32_t a3, uint32_t b0,
                                         uint32_t b1) {
    asm("mma.sync.aligned.m16n8k16.row.col.f32.bf16.bf16.f32 {%0,%1,%2,%3}, {%4,%5,%6,%7}, {%8,%9}, {%0,%1,%2,%3};"
        : "+f"(c[0]), "+f"(c[1]), "+f"(c[2]), "+f"(c[3])
        : "r"(a0), "r"(a1), "r"(a2), "r"(a3), "r"(b0), "r"(b1));
}
__device__ __forceinline__ uint4 ldg_stream(const void* p, uint64_t pol) {
    uint4 v;
    asm volatile("ld.global.nc.L1::no_allocate.L2::cache_hint.v4.u32 {%0,%1,%2,%3}, [%4], %5;"
                 : "=r"(v.x), "=r"(v.y), "=r"(v.z), "=r"(v.w)
                 : "l"(p), "l"(pol));
    return v;
}
__device__ __forceinline__ uint32_t ld_relaxed(const uint32_t* p) {
    uint32_t v;
    asm volatile("ld.relaxed.gpu.global.u32 %0, [%1];" : "=r"(v) : "l"(p) : "memory");
    return v;
}
__device__ __forceinline__ uint32_t ld_acquire(const uint32_t* p) {
    uint32_t v;
    asm volatile("ld.acquire.gpu.global.u32 %0, [%1];" : "=r"(v) : "l"(p) : "memory");
    return v;
}
__device__ __forceinline__ void red_add1(uint32_t* p) {
    asm volatile("red.relaxed.gpu.global.add.u32 [%0], 1;" ::"l"(p) : "memory");
}
__device__ __forceinline__ float bf_lo(uint32_t w) { return __uint_as_float(w << 16); }
__device__ __forceinline__ float bf_hi(uint32_t w) { return __uint_as_float(w & 0xffff0000u); }
__device__ __forceinline__ float bf16_round(float v) { return __bfloat162float(__float2bfloat16_rn(v)); }
__device__ __forceinline__ uint32_t bf16_bits(float v) { return (uint32_t)__bfloat16_as_ushort(__float2bfloat16_rn(v)); }
__device__ __forceinline__ uint32_t enc(float v) {
    uint32_t b = __float_as_uint(v);
    if (b == 0xffffffffu) b = 0x7fffffffu;
    return ~b;
}

template <bool POLL>
__device__ __forceinline__ void reduce_slots(const uint32_t* slot, __nv_bfloat16* out, int br, int idx, int lane) {
    uint4 v[8];
    uint32_t pending = 0xffu;
    for (int it = 0; pending; it++) {
        if (it >= SPIN_LIMIT) __trap();
#pragma unroll
        for (int i = 0; i < 8; i++) {
            if (pending & (1u << i)) {
                asm volatile("ld.relaxed.gpu.global.v4.u32 {%0,%1,%2,%3}, [%4];"
                             : "=r"(v[i].x), "=r"(v[i].y), "=r"(v[i].z), "=r"(v[i].w)
                             : "l"(slot + i * 8 * 16)
                             : "memory");
            }
        }
#pragma unroll
        for (int i = 0; i < 8; i++) {
            if (!POLL || (v[i].x != 0u && v[i].y != 0u && v[i].z != 0u && v[i].w != 0u)) pending &= ~(1u << i);
        }
    }
    float s0 = 0.f, s1 = 0.f, s2 = 0.f, s3 = 0.f;
#pragma unroll
    for (int i = 0; i < 8; i++) {
        s0 += __uint_as_float(~v[i].x);
        s1 += __uint_as_float(~v[i].y);
        s2 += __uint_as_float(~v[i].z);
        s3 += __uint_as_float(~v[i].w);
    }
    __syncwarp();
#pragma unroll
    for (int o = 4; o < 32; o <<= 1) {
        s0 += __shfl_xor_sync(0xffffffffu, s0, o);
        s1 += __shfl_xor_sync(0xffffffffu, s1, o);
        s2 += __shfl_xor_sync(0xffffffffu, s2, o);
        s3 += __shfl_xor_sync(0xffffffffu, s3, o);
    }
    if (lane < 8) {
        const uint32_t w = (lane < 4) ? (bf16_bits(s0) | (bf16_bits(s2) << 16)) : (bf16_bits(s1) | (bf16_bits(s3) << 16));
        __nv_bfloat16* op = out + (idx >> 5) * (2 * D_MODEL) + br * D_MODEL + (idx & 31) * 16 + lane * 2;
        *reinterpret_cast<uint32_t*>(op) = w;
    }
}

__device__ __forceinline__ uint32_t* slot_ptr(int br, int idx, int lane) {
    return g_part + ((size_t)(br * 64 + idx) * 64) * 16 + (lane >> 2) * 16 + (lane & 3) * 4;
}

template <bool FUSED>
__global__ void __cluster_dims__(2, 1, 1) __launch_bounds__(NTHREADS, 1) fused_decode_kernel(const __grid_constant__ Params p) {
    extern __shared__ __align__(1024) unsigned char smem[];
    const uint32_t sbase = smem_u32(smem);
    const int cta = blockIdx.x;
    const int rank = cta & 1;
    const int br = cta >> 6;
    const int h = (cta >> 1) & 31;
    const int tid = threadIdx.x;
    const int warp = tid >> 5;
    const int lane = tid & 31;
    const uint32_t bar_full = sbase + SM_BARS;
    const uint32_t bar_empty = bar_full + NSTAGES * 8;
    const uint32_t bar_x = bar_empty + NSTAGES * 8;

    uint64_t pol;
    asm volatile("createpolicy.fractional.L2::evict_first.b64 %0, 1.0;" : "=l"(pol));

    if (warp == NCW) {
        const long long t_start = clock64();
        const size_t kvoff = ((size_t)(rank * NH + h) * SK + (SK - WIN)) * DH;
        const char* kb = (const char*)(p.k[br] + kvoff);
        const char* vb = (const char*)(p.v[br] + kvoff);
        if (lane == 0) {
#pragma unroll
            for (int i = 0; i < NSTAGES; i++) {
                mbar_init(bar_full + i * 8, 1);
                mbar_init(bar_empty + i * 8, NCW);
            }
            mbar_init(bar_x, 1);
            mbar_init(bar_x + 8, 1);
            asm volatile("fence.mbarrier_init.release.cluster;" ::: "memory");
            asm volatile("fence.proxy.async.shared::cta;" ::: "memory");
            mbar_expect_tx(bar_x, 128 * 4);
            mbar_expect_tx(bar_x + 8, 64 * 4);
#pragma unroll
            for (int i = 0; i < EARLY_STAGES; i++) {
                mbar_expect_tx(bar_full + i * 8, CHUNK_BYTES);
                bulk_load(sbase + SM_RING + i * CHUNK_BYTES, kb + (size_t)i * CHUNK_BYTES, CHUNK_BYTES, bar_full + i * 8, pol);
            }
            asm volatile("prefetch.tensormap [%0];" ::"l"(&p.wo_map[br]) : "memory");
        }
        __syncwarp();
        asm volatile("barrier.cluster.arrive.relaxed.aligned;" ::: "memory");

        const int idx = cta & 63;
        uint32_t* slot = slot_ptr(br, idx, lane);
        uint32_t* done_ctr = g_ctr + br * 128;
        uint32_t* init_ctr = done_ctr + 64;
        uint32_t done_base = 0, init_base = 0;
        if (FUSED) {
            done_base = ld_relaxed(done_ctr) & ~63u;
            init_base = ld_relaxed(init_ctr) & ~63u;
#pragma unroll
            for (int i = 0; i < 8; i++)
                asm volatile("st.relaxed.gpu.global.v4.u32 [%0], {%1,%1,%1,%1};" ::"l"(slot + i * 8 * 16), "r"(0u) : "memory");
            __syncwarp();
            if (lane == 0) {
                asm volatile("fence.acq_rel.gpu;" ::: "memory");
                red_add1(init_ctr);
            }
        }
        if (lane == 0) {
            while (clock64() - t_start < RAMP_CYCLES) {
            }
#pragma unroll
            for (int i = EARLY_STAGES; i < NSTAGES; i++) {
                mbar_expect_tx(bar_full + i * 8, CHUNK_BYTES);
                bulk_load(sbase + SM_RING + i * CHUNK_BYTES, kb + (size_t)i * CHUNK_BYTES, CHUNK_BYTES, bar_full + i * 8, pol);
            }
            if (FUSED) {
                for (int it = 0; ld_acquire(init_ctr) - init_base < 64u; it++)
                    if (it >= SPIN_LIMIT) __trap();
            }
            int s = 0;
            uint32_t ph = 0;
            for (int i = NSTAGES; i < 2 * KCHUNKS + WOCHUNKS; i++) {
                mbar_wait(bar_empty + s * 8, ph);
                if (i < 2 * KCHUNKS) {
                    const char* src = (i < KCHUNKS) ? kb + (size_t)i * CHUNK_BYTES : vb + (size_t)(i - KCHUNKS) * CHUNK_BYTES;
                    mbar_expect_tx(bar_full + s * 8, CHUNK_BYTES);
                    bulk_load(sbase + SM_RING + s * CHUNK_BYTES, src, CHUNK_BYTES, bar_full + s * 8, pol);
                } else {
                    const int n = i - NSTAGES + WO_LAG;
                    mbar_wait(bar_empty + (n % NSTAGES) * 8, (n / NSTAGES) & 1);
                    mbar_expect_tx(bar_full + s * 8, CHUNK_BYTES);
#pragma unroll
                    for (int w = 0; w < 4; w++)
                        tensor_load_2d(sbase + SM_RING + s * CHUNK_BYTES + w * 8192, &p.wo_map[br],
                                       ((i - 2 * KCHUNKS) * 4 + w) * 64, h * DH + rank * 64, bar_full + s * 8, pol);
                }
                if (++s == NSTAGES) { s = 0; ph ^= 1; }
            }
        }
        __syncwarp();
        asm volatile("barrier.cluster.wait.acquire.aligned;" ::: "memory");
        if (FUSED) {
            asm volatile("bar.sync 2, %0;" ::"n"(NTHREADS) : "memory");
            if (lane == 0) {
                for (int it = 0; ld_relaxed(done_ctr) - done_base < (uint32_t)(64 - GATE_SLACK); it++)
                    if (it >= SPIN_LIMIT) __trap();
            }
            __syncwarp();
            reduce_slots<true>(slot, p.out, br, idx, lane);
        }
        return;
    }

    const int g = lane >> 2;
    const int t = lane & 3;
    float* red = reinterpret_cast<float*>(smem + SM_RED);
    const uint32_t peer = rank ^ 1;

    {
        asm volatile("barrier.cluster.arrive.relaxed.aligned;" ::: "memory");
        const int rg = tid >> 4, cg = tid & 15;
        const int k0 = rank * 256 + rg * 16;
        const __nv_bfloat16* wp = p.wq[br] + (size_t)k0 * (NH * DH) + h * DH + cg * 8;
        uint4 w[16];
#pragma unroll
        for (int i = 0; i < 16; i++) w[i] = ldg_stream(wp + (size_t)i * (NH * DH), pol);
        uint4 xa[2][2];
#pragma unroll
        for (int b = 0; b < 2; b++) {
            const uint4* xp = reinterpret_cast<const uint4*>(p.x[br] + b * D_MODEL + k0);
            xa[b][0] = __ldg(xp);
            xa[b][1] = __ldg(xp + 1);
        }
        float acc[2][8];
#pragma unroll
        for (int j = 0; j < 8; j++) { acc[0][j] = 0.f; acc[1][j] = 0.f; }
#pragma unroll
        for (int i = 0; i < 16; i++) {
            float xv[2];
#pragma unroll
            for (int b = 0; b < 2; b++) {
                const uint4 q4 = xa[b][i >> 3];
                const int wi = (i >> 1) & 3;
                const uint32_t ww = wi == 0 ? q4.x : wi == 1 ? q4.y : wi == 2 ? q4.z : q4.w;
                xv[b] = (i & 1) ? bf_hi(ww) : bf_lo(ww);
            }
            const uint32_t ws[4] = {w[i].x, w[i].y, w[i].z, w[i].w};
#pragma unroll
            for (int j = 0; j < 4; j++) {
                const float lo = bf_lo(ws[j]), hi = bf_hi(ws[j]);
                acc[0][2 * j] = fmaf(xv[0], lo, acc[0][2 * j]);
                acc[0][2 * j + 1] = fmaf(xv[0], hi, acc[0][2 * j + 1]);
                acc[1][2 * j] = fmaf(xv[1], lo, acc[1][2 * j]);
                acc[1][2 * j + 1] = fmaf(xv[1], hi, acc[1][2 * j + 1]);
            }
        }
        const bool hi16 = lane >= 16;
        float mine[8];
#pragma unroll
        for (int j = 0; j < 8; j++) {
            const float send = hi16 ? acc[0][j] : acc[1][j];
            const float keep = hi16 ? acc[1][j] : acc[0][j];
            mine[j] = keep + __shfl_xor_sync(0xffffffffu, send, 16);
        }
        float4* dst = reinterpret_cast<float4*>(red + warp * 256 + (hi16 ? 128 : 0) + cg * 8);
        dst[0] = make_float4(mine[0], mine[1], mine[2], mine[3]);
        dst[1] = make_float4(mine[4], mine[5], mine[6], mine[7]);
        asm volatile("barrier.cluster.wait.acquire.aligned;" ::: "memory");
        consumer_bar();
        float s = 0.f;
#pragma unroll
        for (int ww = 0; ww < NCW; ww++) s += red[ww * 256 + tid];
        const int b = tid >> 7, col = tid & 127;
        if (b != rank) {
            st_async_u32(mapa(sbase + SM_QX + col * 4, peer), __float_as_uint(s), mapa(bar_x, peer));
        } else {
            mbar_wait_cluster(bar_x, 0);
            const float other = reinterpret_cast<const float*>(smem + SM_QX)[col];
            reinterpret_cast<__nv_bfloat16*>(smem + SM_QS)[col] = __float2bfloat16_rn(s + other);
        }
        consumer_bar();
    }

    uint32_t koff[4];
    uint4 qf[4];
#pragma unroll
    for (int j = 0; j < 4; j++) {
        koff[j] = (uint32_t)((4 * (j ^ (g & 1)) + t) * 16);
        qf[j] = lds128(sbase + SM_QS + koff[j]);
    }

    const int myz = t ^ (g >> 1);
    float sc[KCHUNKS / 4][2];
    {
        const uint32_t rowoff = (uint32_t)((warp * 16 + g) * ROW_BYTES);
#pragma unroll
        for (int c = 0; c < KCHUNKS; c++) {
            const int s = c % NSTAGES;
            mbar_wait(bar_full + s * 8, (c / NSTAGES) & 1);
            const uint32_t base = sbase + SM_RING + s * CHUNK_BYTES + (rowoff ^ (uint32_t)((c & 3) * 2 * ROW_BYTES));
            uint4 lo[4], hi[4];
#pragma unroll
            for (int j = 0; j < 4; j++) {
                lo[j] = lds128(base + koff[j]);
                hi[j] = lds128(base + 8 * ROW_BYTES + koff[j]);
            }
            float a0[4] = {0.f, 0.f, 0.f, 0.f}, a1[4] = {0.f, 0.f, 0.f, 0.f};
#pragma unroll
            for (int j = 0; j < 4; j++) {
                mma_bf16(a0, lo[j].x, hi[j].x, lo[j].y, hi[j].y, qf[j].x, qf[j].y);
                mma_bf16(a1, lo[j].z, hi[j].z, lo[j].w, hi[j].w, qf[j].z, qf[j].w);
            }
            __syncwarp();
            if (lane == 0) mbar_arrive(bar_empty + s * 8);
            const float r0 = (g & 1) ? (a0[1] + a1[1]) : (a0[0] + a1[0]);
            const float r1 = (g & 1) ? (a0[3] + a1[3]) : (a0[2] + a1[2]);
            if ((c & 3) == 0 || (c & 3) == myz) {
                sc[c >> 2][0] = r0;
                sc[c >> 2][1] = r1;
            }
        }
    }

    uint32_t pb[KCHUNKS / 4][2];
    {
        float* wmax = reinterpret_cast<float*>(smem + SM_WMAX);
        float* wsum = reinterpret_cast<float*>(smem + SM_WSUM);
        const float scale = 0.08838834764831845f;
#pragma unroll
        for (int c = 0; c < KCHUNKS / 4; c++) {
            sc[c][0] = bf16_round(bf16_round(sc[c][0]) * scale);
            sc[c][1] = bf16_round(bf16_round(sc[c][1]) * scale);
        }
        float m = sc[0][0];
#pragma unroll
        for (int c = 0; c < KCHUNKS / 4; c++) m = fmaxf(m, fmaxf(sc[c][0], sc[c][1]));
#pragma unroll
        for (int o = 1; o < 32; o <<= 1) m = fmaxf(m, __shfl_xor_sync(0xffffffffu, m, o));
        if (lane == 0) wmax[warp] = m;
        consumer_bar();
#pragma unroll
        for (int ww = 0; ww < NCW; ww++) m = fmaxf(m, wmax[ww]);
        const float LOG2E = 1.4426950408889634f;
        float sum = 0.f;
#pragma unroll
        for (int c = 0; c < KCHUNKS / 4; c++) {
            sc[c][0] = exp2f((sc[c][0] - m) * LOG2E);
            sc[c][1] = exp2f((sc[c][1] - m) * LOG2E);
            sum += sc[c][0] + sc[c][1];
        }
#pragma unroll
        for (int o = 1; o < 32; o <<= 1) sum += __shfl_xor_sync(0xffffffffu, sum, o);
        if (lane == 0) wsum[warp] = sum;
        consumer_bar();
        float tot = 0.f;
#pragma unroll
        for (int ww = 0; ww < NCW; ww++) tot += wsum[ww];
        const float inv = 1.0f / tot;
        const int sh = (g & 1) * 16;
#pragma unroll
        for (int c = 0; c < KCHUNKS / 4; c++) {
            pb[c][0] = bf16_bits(sc[c][0] * inv) << sh;
            pb[c][1] = bf16_bits(sc[c][1] * inv) << sh;
        }
    }

    float acc[8][4];
#pragma unroll
    for (int i = 0; i < 8; i++) { acc[i][0] = 0.f; acc[i][1] = 0.f; acc[i][2] = 0.f; acc[i][3] = 0.f; }
    const int mi = lane >> 3, r8 = lane & 7;
    {
        const uint32_t rowoff = (uint32_t)((warp * 16 + r8 + 8 * (mi >> 1)) * ROW_BYTES + (mi & 1) * 128);
        uint32_t voff[8];
#pragma unroll
        for (int i = 0; i < 8; i++) voff[i] = rowoff + (uint32_t)((i ^ r8) * 16);
#pragma unroll
        for (int c = 0; c < KCHUNKS; c++) {
            const int cc = KCHUNKS + c;
            const int s = cc % NSTAGES;
            mbar_wait(bar_full + s * 8, (cc / NSTAGES) & 1);
            const uint32_t base = sbase + SM_RING + s * CHUNK_BYTES;
            uint32_t a[8][4];
#pragma unroll
            for (int i = 0; i < 8; i++) ldsm_x4_trans(base + voff[i ^ ((c & 3) * 2)], a[i]);
            const uint32_t b0 = ((c & 3) == myz) ? pb[c >> 2][0] : 0u;
            const uint32_t b1 = ((c & 3) == myz) ? pb[c >> 2][1] : 0u;
#pragma unroll
            for (int i = 0; i < 8; i++) mma_bf16(acc[i], a[i][0], a[i][1], a[i][2], a[i][3], b0, b1);
            __syncwarp();
            if (lane == 0) mbar_arrive(bar_empty + s * 8);
        }
    }
    {
#pragma unroll
        for (int hf = 0; hf < 2; hf++) {
            float u[8];
#pragma unroll
            for (int i = 0; i < 8; i++) u[i] = acc[i][2 * hf] + acc[i ^ 1][2 * hf + 1];
            const float v0 = u[0] + __shfl_xor_sync(0xffffffffu, u[2], 1);
            const float v1 = u[1] + __shfl_xor_sync(0xffffffffu, u[3], 1);
            const float v4 = u[4] + __shfl_xor_sync(0xffffffffu, u[6], 1);
            const float v5 = u[5] + __shfl_xor_sync(0xffffffffu, u[7], 1);
            red[warp * 128 + hf * 64 + (2 * t) * 8 + g] = v0 + __shfl_xor_sync(0xffffffffu, v4, 2);
            red[warp * 128 + hf * 64 + (2 * t + 1) * 8 + g] = v1 + __shfl_xor_sync(0xffffffffu, v5, 2);
        }
        consumer_bar();
        if (tid < 128) {
            float s = 0.f;
#pragma unroll
            for (int ww = 0; ww < NCW; ww++) s += red[ww * 128 + tid];
            const uint32_t mine = bf16_bits(s);
            const uint32_t other = __shfl_down_sync(0xffffffffu, mine, 1);
            if ((tid & 1) == 0) {
                const int row = tid & 63;
                const uint32_t dst = (uint32_t)(tid >> 6);
                const uint32_t off = sbase + SM_OX + (uint32_t)((rank * 32 + ((row >> 1) & 3) * 8 + (row >> 3)) * 4);
                st_async_u32(mapa(off, dst), mine | (other << 16), mapa(bar_x + 8, dst));
            }
        }
    }

    {
        uint32_t a[4][4][4];
        {
            constexpr int cc0 = 2 * KCHUNKS, cc1 = 2 * KCHUNKS + 1;
            const int s = (warp < 4) ? (cc0 % NSTAGES) : (cc1 % NSTAGES);
            const uint32_t ph = (warp < 4) ? ((cc0 / NSTAGES) & 1) : ((cc1 / NSTAGES) & 1);
            mbar_wait(bar_full + s * 8, ph);
            const uint32_t base = sbase + SM_RING + s * CHUNK_BYTES + (warp & 3) * 8192 + (uint32_t)((r8 + 8 * (mi >> 1)) * 128);
#pragma unroll
            for (int ks = 0; ks < 4; ks++)
#pragma unroll
                for (int j = 0; j < 4; j++)
                    ldsm_x4_trans(base + (uint32_t)(ks * 16 * 128) + (uint32_t)(((2 * j + (mi & 1)) ^ r8) * 16), a[ks][j]);
        }
        mbar_wait_cluster(bar_x + 8, 0);
        const uint4 o0 = lds128(sbase + SM_OX + (uint32_t)(((g & 1) * 32 + t * 8) * 4));
        const uint4 o1 = lds128(sbase + SM_OX + (uint32_t)(((g & 1) * 32 + t * 8 + 4) * 4));
        const uint32_t ob[8] = {o0.x, o0.y, o0.z, o0.w, o1.x, o1.y, o1.z, o1.w};
        float e[4][4];
#pragma unroll
        for (int ks = 0; ks < 4; ks++) { e[ks][0] = 0.f; e[ks][1] = 0.f; e[ks][2] = 0.f; e[ks][3] = 0.f; }
#pragma unroll
        for (int j = 0; j < 4; j++) {
            const bool on = (g >> 1) == j;
#pragma unroll
            for (int ks = 0; ks < 4; ks++)
                mma_bf16(e[ks], a[ks][j][0], a[ks][j][1], a[ks][j][2], a[ks][j][3], on ? ob[2 * ks] : 0u,
                         on ? ob[2 * ks + 1] : 0u);
        }
        float f[4];
#pragma unroll
        for (int x = 0; x < 4; x++) f[x] = (e[0][x] + e[1][x]) + (e[2][x] + e[3][x]);
#pragma unroll
        for (int b = 0; b < 2; b++) {
            uint32_t* d = g_part + ((size_t)(br * 64 + b * 32 + warp * 4 + t) * 64 + (cta & 63)) * 16 + g * 2;
            asm volatile("st.relaxed.gpu.global.v2.u32 [%0], {%1,%2};" ::"l"(d), "r"(enc(f[b])), "r"(enc(f[2 + b])) : "memory");
        }
        if (FUSED) {
            if (tid == 0) red_add1(g_ctr + br * 128);
            __syncwarp();
            asm volatile("bar.arrive 2, %0;" ::"n"(NTHREADS) : "memory");
        }
    }
}

__global__ void __launch_bounds__(32) reduce_kernel(__nv_bfloat16* out) {
    const int br = blockIdx.x >> 6, idx = blockIdx.x & 63, lane = threadIdx.x;
    reduce_slots<false>(slot_ptr(br, idx, lane), out, br, idx, lane);
}

typedef CUresult (*EncodeTiledFn)(CUtensorMap*, CUtensorMapDataType, cuuint32_t, void*, const cuuint64_t*, const cuuint64_t*,
                                  const cuuint32_t*, const cuuint32_t*, CUtensorMapInterleave, CUtensorMapSwizzle,
                                  CUtensorMapL2promotion, CUtensorMapFloatOOBfill);

}

extern "C" void kernel_launch(void* const* d_in, const int* in_sizes, int n_in, void* d_out, int out_size) {
    (void)in_sizes; (void)n_in; (void)out_size;
    static EncodeTiledFn encode = nullptr;
    static bool fused = true;
    if (!encode) {
        cudaFuncSetAttribute(fused_decode_kernel<true>, cudaFuncAttributeMaxDynamicSharedMemorySize, SM_TOTAL);
        cudaFuncSetAttribute(fused_decode_kernel<false>, cudaFuncAttributeMaxDynamicSharedMemorySize, SM_TOTAL);
        cudaLaunchConfig_t cfg = {};
        cfg.gridDim = dim3(NCTAS);
        cfg.blockDim = dim3(NTHREADS);
        cfg.dynamicSmemBytes = SM_TOTAL;
        cudaLaunchAttribute at[1];
        at[0].id = cudaLaunchAttributeClusterDimension;
        at[0].val.clusterDim.x = 2;
        at[0].val.clusterDim.y = 1;
        at[0].val.clusterDim.z = 1;
        cfg.attrs = at;
        cfg.numAttrs = 1;
        int nclusters = 0;
        if (cudaOccupancyMaxActiveClusters(&nclusters, fused_decode_kernel<true>, &cfg) == cudaSuccess)
            fused = nclusters >= NCTAS / 2;
        else
            (void)cudaGetLastError();
        void* fn = nullptr;
        cudaDriverEntryPointQueryResult qres;
        cudaGetDriverEntryPoint("cuTensorMapEncodeTiled", &fn, cudaEnableDefault, &qres);
        encode = (EncodeTiledFn)fn;
    }
    Params p;
    for (int i = 0; i < 2; i++) {
        p.x[i] = (const __nv_bfloat16*)d_in[5 * i + 0];
        p.k[i] = (const __nv_bfloat16*)d_in[5 * i + 1];
        p.v[i] = (const __nv_bfloat16*)d_in[5 * i + 2];
        p.wq[i] = (const __nv_bfloat16*)d_in[5 * i + 3];
        const cuuint64_t gdim[2] = {(cuuint64_t)D_MODEL, (cuuint64_t)(NH * DH)};
        const cuuint64_t gstride[1] = {(cuuint64_t)D_MODEL * 2};
        const cuuint32_t box[2] = {64u, 64u};
        const cuuint32_t estr[2] = {1u, 1u};
        encode(&p.wo_map[i], CU_TENSOR_MAP_DATA_TYPE_BFLOAT16, 2, d_in[5 * i + 4], gdim, gstride, box, estr,
               CU_TENSOR_MAP_INTERLEAVE_NONE, CU_TENSOR_MAP_SWIZZLE_128B, CU_TENSOR_MAP_L2_PROMOTION_L2_256B,
               CU_TENSOR_MAP_FLOAT_OOB_FILL_NONE);
    }
    p.out = (__nv_bfloat16*)d_out;
    if (fused) {
        fused_decode_kernel<true><<<NCTAS, NTHREADS, SM_TOTAL>>>(p);
    } else {
        fused_decode_kernel<false><<<NCTAS, NTHREADS, SM_TOTAL>>>(p);
        reduce_kernel<<<NCTAS, 32>>>((__nv_bfloat16*)d_out);
    }
}
```

```cpp
#include <cuda_runtime.h>
#include <cuda.h>
#include <cuda_bf16.h>
#include <stdint.h>

namespace {

constexpr int D_MODEL = 512;
constexpr int NH = 32;
constexpr int SK = 8192;
constexpr int DH = 128;
constexpr int WIN = 2048;
constexpr int ROW_BYTES = DH * 2;
constexpr int CHUNK_BYTES = 32768;
constexpr int NSTAGES = 6;
constexpr int EARLY_STAGES = 4;
constexpr int RAMP_CYCLES = 3000;
constexpr int WO_LAG = 2;
constexpr int GATE_SLACK = 2;
constexpr int KCHUNKS = WIN * ROW_BYTES / CHUNK_BYTES;
constexpr int WOCHUNKS = 2;
constexpr int NCW = 8;
constexpr int NCT = NCW * 32;
constexpr int NTHREADS = NCT + 32;
constexpr int NCTAS = 128;
constexpr int SPIN_LIMIT = 1 << 22;

constexpr int SM_RING = 0;
constexpr int SM_RED = NSTAGES * CHUNK_BYTES;
constexpr int SM_QX = SM_RED + NCW * 256 * 4;
constexpr int SM_QS = SM_QX + 128 * 4;
constexpr int SM_OX = SM_QS + 128 * 2;
constexpr int SM_WMAX = SM_OX + 64 * 4;
constexpr int SM_WSUM = SM_WMAX + 32;
constexpr int SM_BARS = SM_WSUM + 32;
constexpr int SM_TOTAL = SM_BARS + (2 * NSTAGES + 2) * 8;

struct Params {
    alignas(64) CUtensorMap wo_map[2];
    const __nv_bfloat16* x[2];
    const __nv_bfloat16* k[2];
    const __nv_bfloat16* v[2];
    const __nv_bfloat16* wq[2];
    __nv_bfloat16* out;
};

__device__ uint32_t g_part[2 * 64 * 64 * 16];
__device__ uint32_t g_ctr[2 * 128];

__device__ __forceinline__ uint32_t smem_u32(const void* p) { return (uint32_t)__cvta_generic_to_shared(p); }
__device__ __forceinline__ void mbar_init(uint32_t bar, uint32_t cnt) {
    asm volatile("mbarrier.init.shared::cta.b64 [%0], %1;" ::"r"(bar), "r"(cnt) : "memory");
}
__device__ __forceinline__ void mbar_expect_tx(uint32_t bar, uint32_t bytes) {
    asm volatile("mbarrier.arrive.expect_tx.shared::cta.b64 _, [%0], %1;" ::"r"(bar), "r"(bytes) : "memory");
}
__device__ __forceinline__ void mbar_arrive(uint32_t bar) {
    asm volatile("mbarrier.arrive.shared::cta.b64 _, [%0];" ::"r"(bar) : "memory");
}
__device__ __forceinline__ bool mbar_try(uint32_t bar, uint32_t parity) {
    uint32_t ok;
    asm volatile(
        "{\n"
        ".reg .pred p;\n"
        "mbarrier.try_wait.parity.shared::cta.b64 p, [%1], %2;\n"
        "selp.u32 %0, 1, 0, p;\n"
        "}\n"
        : "=r"(ok)
        : "r"(bar), "r"(parity)
        : "memory");
    return ok != 0;
}
__device__ __forceinline__ bool mbar_try_cluster(uint32_t bar, uint32_t parity) {
    uint32_t ok;
    asm volatile(
        "{\n"
        ".reg .pred p;\n"
        "mbarrier.try_wait.parity.acquire.cluster.shared::cta.b64 p, [%1], %2;\n"
        "selp.u32 %0, 1, 0, p;\n"
        "}\n"
        : "=r"(ok)
        : "r"(bar), "r"(parity)
        : "memory");
    return ok != 0;
}
__device__ __forceinline__ void mbar_wait(uint32_t bar, uint32_t parity) {
    if (mbar_try(bar, parity)) return;
#pragma unroll 1
    for (int i = 0; i < SPIN_LIMIT; i++)
        if (mbar_try(bar, parity)) return;
    __trap();
}
__device__ __forceinline__ void mbar_wait_cluster(uint32_t bar, uint32_t parity) {
#pragma unroll 1
    for (int i = 0; i < SPIN_LIMIT; i++)
        if (mbar_try_cluster(bar, parity)) return;
    __trap();
}
__device__ __forceinline__ void bulk_load(uint32_t dst, const void* src, uint32_t bytes, uint32_t bar, uint64_t pol) {
    asm volatile(
        "cp.async.bulk.shared::cluster.global.mbarrier::complete_tx::bytes.L2::cache_hint [%0], [%1], %2, [%3], %4;" ::"r"(dst),
        "l"(src), "r"(bytes), "r"(bar), "l"(pol)
        : "memory");
}
__device__ __forceinline__ void tensor_load_2d(uint32_t dst, const CUtensorMap* map, int c0, int c1, uint32_t bar,
                                               uint64_t pol) {
    asm volatile(
        "cp.async.bulk.tensor.2d.shared::cluster.global.tile.mbarrier::complete_tx::bytes.L2::cache_hint "
        "[%0], [%1, {%2, %3}], [%4], %5;" ::"r"(dst),
        "l"(map), "r"(c0), "r"(c1), "r"(bar), "l"(pol)
        : "memory");
}
__device__ __forceinline__ uint32_t mapa(uint32_t addr, uint32_t rank) {
    uint32_t r;
    asm volatile("mapa.shared::cluster.u32 %0, %1, %2;" : "=r"(r) : "r"(addr), "r"(rank));
    return r;
}
__device__ __forceinline__ void st_async_u32(uint32_t raddr, uint32_t v, uint32_t rbar) {
    asm volatile("st.async.shared::cluster.mbarrier::complete_tx::bytes.u32 [%0], %1, [%2];" ::"r"(raddr), "r"(v), "r"(rbar)
                 : "memory");
}
__device__ __forceinline__ void consumer_bar() { asm volatile("bar.sync 1, %0;" ::"n"(NCT) : "memory"); }
__device__ __forceinline__ uint4 lds128(uint32_t a) {
    uint4 v;
    asm volatile("ld.shared.v4.u32 {%0,%1,%2,%3}, [%4];" : "=r"(v.x), "=r"(v.y), "=r"(v.z), "=r"(v.w) : "r"(a));
    return v;
}
__device__ __forceinline__ void ldsm_x4_trans(uint32_t a, uint32_t (&r)[4]) {
    asm volatile("ldmatrix.sync.aligned.m8n8.x4.trans.shared.b16 {%0,%1,%2,%3}, [%4];"
                 : "=r"(r[0]), "=r"(r[1]), "=r"(r[2]), "=r"(r[3])
                 : "r"(a));
}
__device__ __forceinline__ void mma_bf16(float (&c)[4], uint32_t a0, uint32_t a1, uint32_t a2, uint32_t a3, uint32_t b0,
                                         uint32_t b1) {
    asm("mma.sync.aligned.m16n8k16.row.col.f32.bf16.bf16.f32 {%0,%1,%2,%3}, {%4,%5,%6,%7}, {%8,%9}, {%0,%1,%2,%3};"
        : "+f"(c[0]), "+f"(c[1]), "+f"(c[2]), "+f"(c[3])
        : "r"(a0), "r"(a1), "r"(a2), "r"(a3), "r"(b0), "r"(b1));
}
__device__ __forceinline__ uint4 ldg_stream(const void* p, uint64_t pol) {
    uint4 v;
    asm volatile("ld.global.nc.L1::no_allocate.L2::cache_hint.v4.u32 {%0,%1,%2,%3}, [%4], %5;"
                 : "=r"(v.x), "=r"(v.y), "=r"(v.z), "=r"(v.w)
                 : "l"(p), "l"(pol));
    return v;
}
__device__ __forceinline__ uint32_t ld_relaxed(const uint32_t* p) {
    uint32_t v;
    asm volatile("ld.relaxed.gpu.global.u32 %0, [%1];" : "=r"(v) : "l"(p) : "memory");
    return v;
}
__device__ __forceinline__ uint32_t ld_acquire(const uint32_t* p) {
    uint32_t v;
    asm volatile("ld.acquire.gpu.global.u32 %0, [%1];" : "=r"(v) : "l"(p) : "memory");
    return v;
}
__device__ __forceinline__ void red_add1(uint32_t* p) {
    asm volatile("red.relaxed.gpu.global.add.u32 [%0], 1;" ::"l"(p) : "memory");
}
__device__ __forceinline__ float bf_lo(uint32_t w) { return __uint_as_float(w << 16); }
__device__ __forceinline__ float bf_hi(uint32_t w) { return __uint_as_float(w & 0xffff0000u); }
__device__ __forceinline__ float bf16_round(float v) { return __bfloat162float(__float2bfloat16_rn(v)); }
__device__ __forceinline__ uint32_t bf16_bits(float v) { return (uint32_t)__bfloat16_as_ushort(__float2bfloat16_rn(v)); }
__device__ __forceinline__ uint32_t enc(float v) {
    uint32_t b = __float_as_uint(v);
    if (b == 0xffffffffu) b = 0x7fffffffu;
    return ~b;
}

template <bool POLL>
__device__ __forceinline__ void reduce_slots(const uint32_t* slot, __nv_bfloat16* out, int br, int idx, int lane,
                                             const uint32_t* ctr, uint32_t base) {
    uint4 v[8];
    uint32_t pending = 0xffu;
    uint32_t next = 32;
    for (int it = 0;; it++) {
        if (it >= SPIN_LIMIT) __trap();
        if (POLL && next < (uint32_t)(64 - GATE_SLACK + 1)) {
            uint32_t c = 0;
            if (lane == 0) c = ld_relaxed(ctr) - base;
            c = __shfl_sync(0xffffffffu, c, 0);
            if (c < next) continue;
            next = (c >= (uint32_t)(64 - GATE_SLACK)) ? 64u : min(c + (64u - c) / 2u, (uint32_t)(64 - GATE_SLACK));
        }
#pragma unroll
        for (int i = 0; i < 8; i++) {
            if (pending & (1u << i)) {
                asm volatile("ld.relaxed.gpu.global.v4.u32 {%0,%1,%2,%3}, [%4];"
                             : "=r"(v[i].x), "=r"(v[i].y), "=r"(v[i].z), "=r"(v[i].w)
                             : "l"(slot + i * 8 * 16)
                             : "memory");
            }
        }
#pragma unroll
        for (int i = 0; i < 8; i++) {
            if (!POLL || (v[i].x != 0u && v[i].y != 0u && v[i].z != 0u && v[i].w != 0u)) pending &= ~(1u << i);
        }
        if (__all_sync(0xffffffffu, pending == 0u)) break;
    }
    float s0 = 0.f, s1 = 0.f, s2 = 0.f, s3 = 0.f;
#pragma unroll
    for (int i = 0; i < 8; i++) {
        s0 += __uint_as_float(~v[i].x);
        s1 += __uint_as_float(~v[i].y);
        s2 += __uint_as_float(~v[i].z);
        s3 += __uint_as_float(~v[i].w);
    }
    __syncwarp();
#pragma unroll
    for (int o = 4; o < 32; o <<= 1) {
        s0 += __shfl_xor_sync(0xffffffffu, s0, o);
        s1 += __shfl_xor_sync(0xffffffffu, s1, o);
        s2 += __shfl_xor_sync(0xffffffffu, s2, o);
        s3 += __shfl_xor_sync(0xffffffffu, s3, o);
    }
    if (lane < 8) {
        const uint32_t w = (lane < 4) ? (bf16_bits(s0) | (bf16_bits(s2) << 16)) : (bf16_bits(s1) | (bf16_bits(s3) << 16));
        __nv_bfloat16* op = out + (idx >> 5) * (2 * D_MODEL) + br * D_MODEL + (idx & 31) * 16 + lane * 2;
        *reinterpret_cast<uint32_t*>(op) = w;
    }
}

__device__ __forceinline__ uint32_t* slot_ptr(int br, int idx, int lane) {
    return g_part + ((size_t)(br * 64 + idx) * 64) * 16 + (lane >> 2) * 16 + (lane & 3) * 4;
}

template <bool FUSED>
__global__ void __cluster_dims__(2, 1, 1) __launch_bounds__(NTHREADS, 1) fused_decode_kernel(const __grid_constant__ Params p) {
    extern __shared__ __align__(1024) unsigned char smem[];
    const uint32_t sbase = smem_u32(smem);
    const int cta = blockIdx.x;
    const int rank = cta & 1;
    const int br = cta >> 6;
    const int h = (cta >> 1) & 31;
    const int tid = threadIdx.x;
    const int warp = tid >> 5;
    const int lane = tid & 31;
    const uint32_t bar_full = sbase + SM_BARS;
    const uint32_t bar_empty = bar_full + NSTAGES * 8;
    const uint32_t bar_x = bar_empty + NSTAGES * 8;

    uint64_t pol;
    asm volatile("createpolicy.fractional.L2::evict_first.b64 %0, 1.0;" : "=l"(pol));

    if (warp == NCW) {
        const long long t_start = clock64();
        const size_t kvoff = ((size_t)(rank * NH + h) * SK + (SK - WIN)) * DH;
        const char* kb = (const char*)(p.k[br] + kvoff);
        const char* vb = (const char*)(p.v[br] + kvoff);
        if (lane == 0) {
#pragma unroll
            for (int i = 0; i < NSTAGES; i++) {
                mbar_init(bar_full + i * 8, 1);
                mbar_init(bar_empty + i * 8, NCW);
            }
            mbar_init(bar_x, 1);
            mbar_init(bar_x + 8, 1);
            asm volatile("fence.mbarrier_init.release.cluster;" ::: "memory");
            asm volatile("fence.proxy.async.shared::cta;" ::: "memory");
            mbar_expect_tx(bar_x, 128 * 4);
            mbar_expect_tx(bar_x + 8, 64 * 4);
#pragma unroll
            for (int i = 0; i < EARLY_STAGES; i++) {
                mbar_expect_tx(bar_full + i * 8, CHUNK_BYTES);
                bulk_load(sbase + SM_RING + i * CHUNK_BYTES, kb + (size_t)i * CHUNK_BYTES, CHUNK_BYTES, bar_full + i * 8, pol);
            }
            asm volatile("prefetch.tensormap [%0];" ::"l"(&p.wo_map[br]) : "memory");
        }
        __syncwarp();
        asm volatile("barrier.cluster.arrive.relaxed.aligned;" ::: "memory");

        const int idx = cta & 63;
        uint32_t* slot = slot_ptr(br, idx, lane);
        uint32_t* done_ctr = g_ctr + br * 128;
        uint32_t* init_ctr = done_ctr + 64;
        uint32_t done_base = 0, init_base = 0;
        if (FUSED) {
            done_base = ld_relaxed(done_ctr) & ~63u;
            init_base = ld_relaxed(init_ctr) & ~63u;
#pragma unroll
            for (int i = 0; i < 8; i++)
                asm volatile("st.relaxed.gpu.global.v4.u32 [%0], {%1,%1,%1,%1};" ::"l"(slot + i * 8 * 16), "r"(0u) : "memory");
            __syncwarp();
            if (lane == 0) {
                asm volatile("fence.acq_rel.gpu;" ::: "memory");
                red_add1(init_ctr);
            }
        }
        if (lane == 0) {
            while (clock64() - t_start < RAMP_CYCLES) {
            }
#pragma unroll
            for (int i = EARLY_STAGES; i < NSTAGES; i++) {
                mbar_expect_tx(bar_full + i * 8, CHUNK_BYTES);
                bulk_load(sbase + SM_RING + i * CHUNK_BYTES, kb + (size_t)i * CHUNK_BYTES, CHUNK_BYTES, bar_full + i * 8, pol);
            }
            if (FUSED) {
                for (int it = 0; ld_acquire(init_ctr) - init_base < 64u; it++)
                    if (it >= SPIN_LIMIT) __trap();
            }
            int s = 0;
            uint32_t ph = 0;
            for (int i = NSTAGES; i < 2 * KCHUNKS + WOCHUNKS; i++) {
                mbar_wait(bar_empty + s * 8, ph);
                if (i < 2 * KCHUNKS) {
                    const char* src = (i < KCHUNKS) ? kb + (size_t)i * CHUNK_BYTES : vb + (size_t)(i - KCHUNKS) * CHUNK_BYTES;
                    mbar_expect_tx(bar_full + s * 8, CHUNK_BYTES);
                    bulk_load(sbase + SM_RING + s * CHUNK_BYTES, src, CHUNK_BYTES, bar_full + s * 8, pol);
                } else {
                    const int n = i - NSTAGES + WO_LAG;
                    mbar_wait(bar_empty + (n % NSTAGES) * 8, (n / NSTAGES) & 1);
                    mbar_expect_tx(bar_full + s * 8, CHUNK_BYTES);
#pragma unroll
                    for (int w = 0; w < 4; w++)
                        tensor_load_2d(sbase + SM_RING + s * CHUNK_BYTES + w * 8192, &p.wo_map[br],
                                       ((i - 2 * KCHUNKS) * 4 + w) * 64, h * DH + rank * 64, bar_full + s * 8, pol);
                }
                if (++s == NSTAGES) { s = 0; ph ^= 1; }
            }
        }
        __syncwarp();
        asm volatile("barrier.cluster.wait.acquire.aligned;" ::: "memory");
        if (FUSED) {
            reduce_slots<true>(slot, p.out, br, idx, lane, done_ctr, done_base);
        }
        return;
    }

    const int g = lane >> 2;
    const int t = lane & 3;
    float* red = reinterpret_cast<float*>(smem + SM_RED);
    const uint32_t peer = rank ^ 1;

    {
        asm volatile("barrier.cluster.arrive.relaxed.aligned;" ::: "memory");
        const int rg = tid >> 4, cg = tid & 15;
        const int k0 = rank * 256 + rg * 16;
        const __nv_bfloat16* wp = p.wq[br] + (size_t)k0 * (NH * DH) + h * DH + cg * 8;
        uint4 w[16];
#pragma unroll
        for (int i = 0; i < 16; i++) w[i] = ldg_stream(wp + (size_t)i * (NH * DH), pol);
        uint4 xa[2][2];
#pragma unroll
        for (int b = 0; b < 2; b++) {
            const uint4* xp = reinterpret_cast<const uint4*>(p.x[br] + b * D_MODEL + k0);
            xa[b][0] = __ldg(xp);
            xa[b][1] = __ldg(xp + 1);
        }
        float acc[2][8];
#pragma unroll
        for (int j = 0; j < 8; j++) { acc[0][j] = 0.f; acc[1][j] = 0.f; }
#pragma unroll
        for (int i = 0; i < 16; i++) {
            float xv[2];
#pragma unroll
            for (int b = 0; b < 2; b++) {
                const uint4 q4 = xa[b][i >> 3];
                const int wi = (i >> 1) & 3;
                const uint32_t ww = wi == 0 ? q4.x : wi == 1 ? q4.y : wi == 2 ? q4.z : q4.w;
                xv[b] = (i & 1) ? bf_hi(ww) : bf_lo(ww);
            }
            const uint32_t ws[4] = {w[i].x, w[i].y, w[i].z, w[i].w};
#pragma unroll
            for (int j = 0; j < 4; j++) {
                const float lo = bf_lo(ws[j]), hi = bf_hi(ws[j]);
                acc[0][2 * j] = fmaf(xv[0], lo, acc[0][2 * j]);
                acc[0][2 * j + 1] = fmaf(xv[0], hi, acc[0][2 * j + 1]);
                acc[1][2 * j] = fmaf(xv[1], lo, acc[1][2 * j]);
                acc[1][2 * j + 1] = fmaf(xv[1], hi, acc[1][2 * j + 1]);
            }
        }
        const bool hi16 = lane >= 16;
        float mine[8];
#pragma unroll
        for (int j = 0; j < 8; j++) {
            const float send = hi16 ? acc[0][j] : acc[1][j];
            const float keep = hi16 ? acc[1][j] : acc[0][j];
            mine[j] = keep + __shfl_xor_sync(0xffffffffu, send, 16);
        }
        float4* dst = reinterpret_cast<float4*>(red + warp * 256 + (hi16 ? 128 : 0) + cg * 8);
        dst[0] = make_float4(mine[0], mine[1], mine[2], mine[3]);
        dst[1] = make_float4(mine[4], mine[5], mine[6], mine[7]);
        asm volatile("barrier.cluster.wait.acquire.aligned;" ::: "memory");
        consumer_bar();
        float s = 0.f;
#pragma unroll
        for (int ww = 0; ww < NCW; ww++) s += red[ww * 256 + tid];
        const int b = tid >> 7, col = tid & 127;
        if (b != rank) {
            st_async_u32(mapa(sbase + SM_QX + col * 4, peer), __float_as_uint(s), mapa(bar_x, peer));
        } else {
            mbar_wait_cluster(bar_x, 0);
            const float other = reinterpret_cast<const float*>(smem + SM_QX)[col];
            reinterpret_cast<__nv_bfloat16*>(smem + SM_QS)[col] = __float2bfloat16_rn(s + other);
        }
        consumer_bar();
    }

    uint32_t koff[4];
    uint4 qf[4];
#pragma unroll
    for (int j = 0; j < 4; j++) {
        koff[j] = (uint32_t)((4 * (j ^ (g & 1)) + t) * 16);
        qf[j] = lds128(sbase + SM_QS + koff[j]);
    }

    const int myz = t ^ (g >> 1);
    float sc[KCHUNKS / 4][2];
    {
        const uint32_t rowoff = (uint32_t)((warp * 16 + g) * ROW_BYTES);
#pragma unroll
        for (int c = 0; c < KCHUNKS; c++) {
            const int s = c % NSTAGES;
            mbar_wait(bar_full + s * 8, (c / NSTAGES) & 1);
            const uint32_t base = sbase + SM_RING + s * CHUNK_BYTES + (rowoff ^ (uint32_t)((c & 3) * 2 * ROW_BYTES));
            uint4 lo[4], hi[4];
#pragma unroll
            for (int j = 0; j < 4; j++) {
                lo[j] = lds128(base + koff[j]);
                hi[j] = lds128(base + 8 * ROW_BYTES + koff[j]);
            }
            float a0[4] = {0.f, 0.f, 0.f, 0.f}, a1[4] = {0.f, 0.f, 0.f, 0.f};
#pragma unroll
            for (int j = 0; j < 4; j++) {
                mma_bf16(a0, lo[j].x, hi[j].x, lo[j].y, hi[j].y, qf[j].x, qf[j].y);
                mma_bf16(a1, lo[j].z, hi[j].z, lo[j].w, hi[j].w, qf[j].z, qf[j].w);
            }
            __syncwarp();
            if (lane == 0) mbar_arrive(bar_empty + s * 8);
            const float r0 = (g & 1) ? (a0[1] + a1[1]) : (a0[0] + a1[0]);
            const float r1 = (g & 1) ? (a0[3] + a1[3]) : (a0[2] + a1[2]);
            if ((c & 3) == 0 || (c & 3) == myz) {
                sc[c >> 2][0] = r0;
                sc[c >> 2][1] = r1;
            }
        }
    }

    uint32_t pb[KCHUNKS / 4][2];
    {
        float* wmax = reinterpret_cast<float*>(smem + SM_WMAX);
        float* wsum = reinterpret_cast<float*>(smem + SM_WSUM);
        const float scale = 0.08838834764831845f;
#pragma unroll
        for (int c = 0; c < KCHUNKS / 4; c++) {
            sc[c][0] = bf16_round(bf16_round(sc[c][0]) * scale);
            sc[c][1] = bf16_round(bf16_round(sc[c][1]) * scale);
        }
        float m = sc[0][0];
#pragma unroll
        for (int c = 0; c < KCHUNKS / 4; c++) m = fmaxf(m, fmaxf(sc[c][0], sc[c][1]));
#pragma unroll
        for (int o = 1; o < 32; o <<= 1) m = fmaxf(m, __shfl_xor_sync(0xffffffffu, m, o));
        if (lane == 0) wmax[warp] = m;
        consumer_bar();
#pragma unroll
        for (int ww = 0; ww < NCW; ww++) m = fmaxf(m, wmax[ww]);
        const float LOG2E = 1.4426950408889634f;
        float sum = 0.f;
#pragma unroll
        for (int c = 0; c < KCHUNKS / 4; c++) {
            sc[c][0] = exp2f((sc[c][0] - m) * LOG2E);
            sc[c][1] = exp2f((sc[c][1] - m) * LOG2E);
            sum += sc[c][0] + sc[c][1];
        }
#pragma unroll
        for (int o = 1; o < 32; o <<= 1) sum += __shfl_xor_sync(0xffffffffu, sum, o);
        if (lane == 0) wsum[warp] = sum;
        consumer_bar();
        float tot = 0.f;
#pragma unroll
        for (int ww = 0; ww < NCW; ww++) tot += wsum[ww];
        const float inv = 1.0f / tot;
        const int sh = (g & 1) * 16;
#pragma unroll
        for (int c = 0; c < KCHUNKS / 4; c++) {
            pb[c][0] = bf16_bits(sc[c][0] * inv) << sh;
            pb[c][1] = bf16_bits(sc[c][1] * inv) << sh;
        }
    }

    float acc[8][4];
#pragma unroll
    for (int i = 0; i < 8; i++) { acc[i][0] = 0.f; acc[i][1] = 0.f; acc[i][2] = 0.f; acc[i][3] = 0.f; }
    const int mi = lane >> 3, r8 = lane & 7;
    {
        const uint32_t rowoff = (uint32_t)((warp * 16 + r8 + 8 * (mi >> 1)) * ROW_BYTES + (mi & 1) * 128);
        uint32_t voff[8];
#pragma unroll
        for (int i = 0; i < 8; i++) voff[i] = rowoff + (uint32_t)((i ^ r8) * 16);
#pragma unroll
        for (int c = 0; c < KCHUNKS; c++) {
            const int cc = KCHUNKS + c;
            const int s = cc % NSTAGES;
            mbar_wait(bar_full + s * 8, (cc / NSTAGES) & 1);
            const uint32_t base = sbase + SM_RING + s * CHUNK_BYTES;
            uint32_t a[8][4];
#pragma unroll
            for (int i = 0; i < 8; i++) ldsm_x4_trans(base + voff[i ^ ((c & 3) * 2)], a[i]);
            const uint32_t b0 = ((c & 3) == myz) ? pb[c >> 2][0] : 0u;
            const uint32_t b1 = ((c & 3) == myz) ? pb[c >> 2][1] : 0u;
#pragma unroll
            for (int i = 0; i < 8; i++) mma_bf16(acc[i], a[i][0], a[i][1], a[i][2], a[i][3], b0, b1);
            __syncwarp();
            if (lane == 0) mbar_arrive(bar_empty + s * 8);
        }
    }
    {
#pragma unroll
        for (int hf = 0; hf < 2; hf++) {
            float u[8];
#pragma unroll
            for (int i = 0; i < 8; i++) u[i] = acc[i][2 * hf] + acc[i ^ 1][2 * hf + 1];
            const float v0 = u[0] + __shfl_xor_sync(0xffffffffu, u[2], 1);
            const float v1 = u[1] + __shfl_xor_sync(0xffffffffu, u[3], 1);
            const float v4 = u[4] + __shfl_xor_sync(0xffffffffu, u[6], 1);
            const float v5 = u[5] + __shfl_xor_sync(0xffffffffu, u[7], 1);
            red[warp * 128 + hf * 64 + (2 * t) * 8 + g] = v0 + __shfl_xor_sync(0xffffffffu, v4, 2);
            red[warp * 128 + hf * 64 + (2 * t + 1) * 8 + g] = v1 + __shfl_xor_sync(0xffffffffu, v5, 2);
        }
        consumer_bar();
        if (tid < 128) {
            float s = 0.f;
#pragma unroll
            for (int ww = 0; ww < NCW; ww++) s += red[ww * 128 + tid];
            const uint32_t mine = bf16_bits(s);
            const uint32_t other = __shfl_down_sync(0xffffffffu, mine, 1);
            if ((tid & 1) == 0) {
                const int row = tid & 63;
                const uint32_t dst = (uint32_t)(tid >> 6);
                const uint32_t off = sbase + SM_OX + (uint32_t)((rank * 32 + ((row >> 1) & 3) * 8 + (row >> 3)) * 4);
                st_async_u32(mapa(off, dst), mine | (other << 16), mapa(bar_x + 8, dst));
            }
        }
    }

    {
        uint32_t a[4][4][4];
        {
            constexpr int cc0 = 2 * KCHUNKS, cc1 = 2 * KCHUNKS + 1;
            const int s = (warp < 4) ? (cc0 % NSTAGES) : (cc1 % NSTAGES);
            const uint32_t ph = (warp < 4) ? ((cc0 / NSTAGES) & 1) : ((cc1 / NSTAGES) & 1);
            mbar_wait(bar_full + s * 8, ph);
            const uint32_t base = sbase + SM_RING + s * CHUNK_BYTES + (warp & 3) * 8192 + (uint32_t)((r8 + 8 * (mi >> 1)) * 128);
#pragma unroll
            for (int ks = 0; ks < 4; ks++)
#pragma unroll
                for (int j = 0; j < 4; j++)
                    ldsm_x4_trans(base + (uint32_t)(ks * 16 * 128) + (uint32_t)(((2 * j + (mi & 1)) ^ r8) * 16), a[ks][j]);
        }
        mbar_wait_cluster(bar_x + 8, 0);
        const uint4 o0 = lds128(sbase + SM_OX + (uint32_t)(((g & 1) * 32 + t * 8) * 4));
        const uint4 o1 = lds128(sbase + SM_OX + (uint32_t)(((g & 1) * 32 + t * 8 + 4) * 4));
        const uint32_t ob[8] = {o0.x, o0.y, o0.z, o0.w, o1.x, o1.y, o1.z, o1.w};
        float e[4][4];
#pragma unroll
        for (int ks = 0; ks < 4; ks++) { e[ks][0] = 0.f; e[ks][1] = 0.f; e[ks][2] = 0.f; e[ks][3] = 0.f; }
#pragma unroll
        for (int j = 0; j < 4; j++) {
            const bool on = (g >> 1) == j;
#pragma unroll
            for (int ks = 0; ks < 4; ks++)
                mma_bf16(e[ks], a[ks][j][0], a[ks][j][1], a[ks][j][2], a[ks][j][3], on ? ob[2 * ks] : 0u,
                         on ? ob[2 * ks + 1] : 0u);
        }
        float f[4];
#pragma unroll
        for (int x = 0; x < 4; x++) f[x] = (e[0][x] + e[1][x]) + (e[2][x] + e[3][x]);
#pragma unroll
        for (int b = 0; b < 2; b++) {
            uint32_t* d = g_part + ((size_t)(br * 64 + b * 32 + warp * 4 + t) * 64 + (cta & 63)) * 16 + g * 2;
            asm volatile("st.relaxed.gpu.global.v2.u32 [%0], {%1,%2};" ::"l"(d), "r"(enc(f[b])), "r"(enc(f[2 + b])) : "memory");
        }
        if (FUSED && tid == 0) red_add1(g_ctr + br * 128);
    }
}

__global__ void __launch_bounds__(32) reduce_kernel(__nv_bfloat16* out) {
    const int br = blockIdx.x >> 6, idx = blockIdx.x & 63, lane = threadIdx.x;
    reduce_slots<false>(slot_ptr(br, idx, lane), out, br, idx, lane, nullptr, 0u);
}

typedef CUresult (*EncodeTiledFn)(CUtensorMap*, CUtensorMapDataType, cuuint32_t, void*, const cuuint64_t*, const cuuint64_t*,
                                  const cuuint32_t*, const cuuint32_t*, CUtensorMapInterleave, CUtensorMapSwizzle,
                                  CUtensorMapL2promotion, CUtensorMapFloatOOBfill);

}

extern "C" void kernel_launch(void* const* d_in, const int* in_sizes, int n_in, void* d_out, int out_size) {
    (void)in_sizes; (void)n_in; (void)out_size;
    static EncodeTiledFn encode = nullptr;
    static bool fused = true;
    if (!encode) {
        cudaFuncSetAttribute(fused_decode_kernel<true>, cudaFuncAttributeMaxDynamicSharedMemorySize, SM_TOTAL);
        cudaFuncSetAttribute(fused_decode_kernel<false>, cudaFuncAttributeMaxDynamicSharedMemorySize, SM_TOTAL);
        cudaLaunchConfig_t cfg = {};
        cfg.gridDim = dim3(NCTAS);
        cfg.blockDim = dim3(NTHREADS);
        cfg.dynamicSmemBytes = SM_TOTAL;
        cudaLaunchAttribute at[1];
        at[0].id = cudaLaunchAttributeClusterDimension;
        at[0].val.clusterDim.x = 2;
        at[0].val.clusterDim.y = 1;
        at[0].val.clusterDim.z = 1;
        cfg.attrs = at;
        cfg.numAttrs = 1;
        int nclusters = 0;
        if (cudaOccupancyMaxActiveClusters(&nclusters, fused_decode_kernel<true>, &cfg) == cudaSuccess)
            fused = nclusters >= NCTAS / 2;
        else
            (void)cudaGetLastError();
        void* fn = nullptr;
        cudaDriverEntryPointQueryResult qres;
        cudaGetDriverEntryPoint("cuTensorMapEncodeTiled", &fn, cudaEnableDefault, &qres);
        encode = (EncodeTiledFn)fn;
    }
    Params p;
    for (int i = 0; i < 2; i++) {
        p.x[i] = (const __nv_bfloat16*)d_in[5 * i + 0];
        p.k[i] = (const __nv_bfloat16*)d_in[5 * i + 1];
        p.v[i] = (const __nv_bfloat16*)d_in[5 * i + 2];
        p.wq[i] = (const __nv_bfloat16*)d_in[5 * i + 3];
        const cuuint64_t gdim[2] = {(cuuint64_t)D_MODEL, (cuuint64_t)(NH * DH)};
        const cuuint64_t gstride[1] = {(cuuint64_t)D_MODEL * 2};
        const cuuint32_t box[2] = {64u, 64u};
        const cuuint32_t estr[2] = {1u, 1u};
        encode(&p.wo_map[i], CU_TENSOR_MAP_DATA_TYPE_BFLOAT16, 2, d_in[5 * i + 4], gdim, gstride, box, estr,
               CU_TENSOR_MAP_INTERLEAVE_NONE, CU_TENSOR_MAP_SWIZZLE_128B, CU_TENSOR_MAP_L2_PROMOTION_L2_256B,
               CU_TENSOR_MAP_FLOAT_OOB_FILL_NONE);
    }
    p.out = (__nv_bfloat16*)d_out;
    if (fused) {
        fused_decode_kernel<true><<<NCTAS, NTHREADS, SM_TOTAL>>>(p);
    } else {
        fused_decode_kernel<false><<<NCTAS, NTHREADS, SM_TOTAL>>>(p);
        reduce_kernel<<<NCTAS, 32>>>((__nv_bfloat16*)d_out);
    }
}
```

```cpp
#include <cuda_runtime.h>
#include <cuda.h>
#include <cuda_bf16.h>
#include <stdint.h>

namespace {

constexpr int D_MODEL = 512;
constexpr int NH = 32;
constexpr int SK = 8192;
constexpr int DH = 128;
constexpr int WIN = 2048;
constexpr int ROW_BYTES = DH * 2;
constexpr int CHUNK_BYTES = 32768;
constexpr int NSTAGES = 6;
constexpr int MAX_INFLIGHT = 4;
constexpr int GATE_SLACK = 2;
constexpr int KCHUNKS = WIN * ROW_BYTES / CHUNK_BYTES;
constexpr int WOCHUNKS = 2;
constexpr int NCW = 8;
constexpr int NCT = NCW * 32;
constexpr int NTHREADS = NCT + 32;
constexpr int NCTAS = 128;
constexpr int SPIN_LIMIT = 1 << 22;

constexpr int SM_RING = 0;
constexpr int SM_RED = NSTAGES * CHUNK_BYTES;
constexpr int SM_QX = SM_RED + NCW * 256 * 4;
constexpr int SM_QS = SM_QX + 128 * 4;
constexpr int SM_OX = SM_QS + 128 * 2;
constexpr int SM_WMAX = SM_OX + 64 * 4;
constexpr int SM_WSUM = SM_WMAX + 32;
constexpr int SM_BARS = SM_WSUM + 32;
constexpr int SM_TOTAL = SM_BARS + (2 * NSTAGES + 2) * 8;

struct Params {
    alignas(64) CUtensorMap wo_map[2];
    const __nv_bfloat16* x[2];
    const __nv_bfloat16* k[2];
    const __nv_bfloat16* v[2];
    const __nv_bfloat16* wq[2];
    __nv_bfloat16* out;
};

__device__ uint32_t g_part[2 * 64 * 64 * 16];
__device__ uint32_t g_ctr[2 * 128];

__device__ __forceinline__ uint32_t smem_u32(const void* p) { return (uint32_t)__cvta_generic_to_shared(p); }
__device__ __forceinline__ void mbar_init(uint32_t bar, uint32_t cnt) {
    asm volatile("mbarrier.init.shared::cta.b64 [%0], %1;" ::"r"(bar), "r"(cnt) : "memory");
}
__device__ __forceinline__ void mbar_expect_tx(uint32_t bar, uint32_t bytes) {
    asm volatile("mbarrier.arrive.expect_tx.shared::cta.b64 _, [%0], %1;" ::"r"(bar), "r"(bytes) : "memory");
}
__device__ __forceinline__ void mbar_arrive(uint32_t bar) {
    asm volatile("mbarrier.arrive.shared::cta.b64 _, [%0];" ::"r"(bar) : "memory");
}
__device__ __forceinline__ bool mbar_try(uint32_t bar, uint32_t parity) {
    uint32_t ok;
    asm volatile(
        "{\n"
        ".reg .pred p;\n"
        "mbarrier.try_wait.parity.shared::cta.b64 p, [%1], %2;\n"
        "selp.u32 %0, 1, 0, p;\n"
        "}\n"
        : "=r"(ok)
        : "r"(bar), "r"(parity)
        : "memory");
    return ok != 0;
}
__device__ __forceinline__ bool mbar_try_cluster(uint32_t bar, uint32_t parity) {
    uint32_t ok;
    asm volatile(
        "{\n"
        ".reg .pred p;\n"
        "mbarrier.try_wait.parity.acquire.cluster.shared::cta.b64 p, [%1], %2;\n"
        "selp.u32 %0, 1, 0, p;\n"
        "}\n"
        : "=r"(ok)
        : "r"(bar), "r"(parity)
        : "memory");
    return ok != 0;
}
__device__ __forceinline__ void mbar_wait(uint32_t bar, uint32_t parity) {
    if (mbar_try(bar, parity)) return;
#pragma unroll 1
    for (int i = 0; i < SPIN_LIMIT; i++)
        if (mbar_try(bar, parity)) return;
    __trap();
}
__device__ __forceinline__ void mbar_wait_cluster(uint32_t bar, uint32_t parity) {
#pragma unroll 1
    for (int i = 0; i < SPIN_LIMIT; i++)
        if (mbar_try_cluster(bar, parity)) return;
    __trap();
}
__device__ __forceinline__ void bulk_load(uint32_t dst, const void* src, uint32_t bytes, uint32_t bar, uint64_t pol) {
    asm volatile(
        "cp.async.bulk.shared::cluster.global.mbarrier::complete_tx::bytes.L2::cache_hint [%0], [%1], %2, [%3], %4;" ::"r"(dst),
        "l"(src), "r"(bytes), "r"(bar), "l"(pol)
        : "memory");
}
__device__ __forceinline__ void tensor_load_2d(uint32_t dst, const CUtensorMap* map, int c0, int c1, uint32_t bar,
                                               uint64_t pol) {
    asm volatile(
        "cp.async.bulk.tensor.2d.shared::cluster.global.tile.mbarrier::complete_tx::bytes.L2::cache_hint "
        "[%0], [%1, {%2, %3}], [%4], %5;" ::"r"(dst),
        "l"(map), "r"(c0), "r"(c1), "r"(bar), "l"(pol)
        : "memory");
}
__device__ __forceinline__ uint32_t mapa(uint32_t addr, uint32_t rank) {
    uint32_t r;
    asm volatile("mapa.shared::cluster.u32 %0, %1, %2;" : "=r"(r) : "r"(addr), "r"(rank));
    return r;
}
__device__ __forceinline__ void st_async_u32(uint32_t raddr, uint32_t v, uint32_t rbar) {
    asm volatile("st.async.shared::cluster.mbarrier::complete_tx::bytes.u32 [%0], %1, [%2];" ::"r"(raddr), "r"(v), "r"(rbar)
                 : "memory");
}
__device__ __forceinline__ void consumer_bar() { asm volatile("bar.sync 1, %0;" ::"n"(NCT) : "memory"); }
__device__ __forceinline__ uint4 lds128(uint32_t a) {
    uint4 v;
    asm volatile("ld.shared.v4.u32 {%0,%1,%2,%3}, [%4];" : "=r"(v.x), "=r"(v.y), "=r"(v.z), "=r"(v.w) : "r"(a));
    return v;
}
__device__ __forceinline__ void ldsm_x4_trans(uint32_t a, uint32_t (&r)[4]) {
    asm volatile("ldmatrix.sync.aligned.m8n8.x4.trans.shared.b16 {%0,%1,%2,%3}, [%4];"
                 : "=r"(r[0]), "=r"(r[1]), "=r"(r[2]), "=r"(r[3])
                 : "r"(a));
}
__device__ __forceinline__ void mma_bf16(float (&c)[4], uint32_t a0, uint32_t a1, uint32_t a2, uint32_t a3, uint32_t b0,
                                         uint32_t b1) {
    asm("mma.sync.aligned.m16n8k16.row.col.f32.bf16.bf16.f32 {%0,%1,%2,%3}, {%4,%5,%6,%7}, {%8,%9}, {%0,%1,%2,%3};"
        : "+f"(c[0]), "+f"(c[1]), "+f"(c[2]), "+f"(c[3])
        : "r"(a0), "r"(a1), "r"(a2), "r"(a3), "r"(b0), "r"(b1));
}
__device__ __forceinline__ uint4 ldg_stream(const void* p, uint64_t pol) {
    uint4 v;
    asm volatile("ld.global.nc.L1::no_allocate.L2::cache_hint.v4.u32 {%0,%1,%2,%3}, [%4], %5;"
                 : "=r"(v.x), "=r"(v.y), "=r"(v.z), "=r"(v.w)
                 : "l"(p), "l"(pol));
    return v;
}
__device__ __forceinline__ uint32_t ld_relaxed(const uint32_t* p) {
    uint32_t v;
    asm volatile("ld.relaxed.gpu.global.u32 %0, [%1];" : "=r"(v) : "l"(p) : "memory");
    return v;
}
__device__ __forceinline__ uint32_t ld_acquire(const uint32_t* p) {
    uint32_t v;
    asm volatile("ld.acquire.gpu.global.u32 %0, [%1];" : "=r"(v) : "l"(p) : "memory");
    return v;
}
__device__ __forceinline__ void red_add1(uint32_t* p) {
    asm volatile("red.relaxed.gpu.global.add.u32 [%0], 1;" ::"l"(p) : "memory");
}
__device__ __forceinline__ float bf_lo(uint32_t w) { return __uint_as_float(w << 16); }
__device__ __forceinline__ float bf_hi(uint32_t w) { return __uint_as_float(w & 0xffff0000u); }
__device__ __forceinline__ float bf16_round(float v) { return __bfloat162float(__float2bfloat16_rn(v)); }
__device__ __forceinline__ uint32_t bf16_bits(float v) { return (uint32_t)__bfloat16_as_ushort(__float2bfloat16_rn(v)); }
__device__ __forceinline__ uint32_t enc(float v) {
    uint32_t b = __float_as_uint(v);
    if (b == 0xffffffffu) b = 0x7fffffffu;
    return ~b;
}

template <bool POLL>
__device__ __forceinline__ void reduce_slots(const uint32_t* slot, __nv_bfloat16* out, int br, int idx, int lane,
                                             const uint32_t* ctr, uint32_t base) {
    uint4 v[8];
    uint32_t pending = 0xffu;
    uint32_t next = 32;
    for (int it = 0;; it++) {
        if (it >= SPIN_LIMIT) __trap();
        if (POLL && next < (uint32_t)(64 - GATE_SLACK + 1)) {
            uint32_t c = 0;
            if (lane == 0) c = ld_relaxed(ctr) - base;
            c = __shfl_sync(0xffffffffu, c, 0);
            if (c < next) continue;
            next = (c >= (uint32_t)(64 - GATE_SLACK)) ? 64u : min(c + (64u - c) / 2u, (uint32_t)(64 - GATE_SLACK));
        }
#pragma unroll
        for (int i = 0; i < 8; i++) {
            if (pending & (1u << i)) {
                asm volatile("ld.relaxed.gpu.global.v4.u32 {%0,%1,%2,%3}, [%4];"
                             : "=r"(v[i].x), "=r"(v[i].y), "=r"(v[i].z), "=r"(v[i].w)
                             : "l"(slot + i * 8 * 16)
                             : "memory");
            }
        }
#pragma unroll
        for (int i = 0; i < 8; i++) {
            if (!POLL || (v[i].x != 0u && v[i].y != 0u && v[i].z != 0u && v[i].w != 0u)) pending &= ~(1u << i);
        }
        if (__all_sync(0xffffffffu, pending == 0u)) break;
    }
    float s0 = 0.f, s1 = 0.f, s2 = 0.f, s3 = 0.f;
#pragma unroll
    for (int i = 0; i < 8; i++) {
        s0 += __uint_as_float(~v[i].x);
        s1 += __uint_as_float(~v[i].y);
        s2 += __uint_as_float(~v[i].z);
        s3 += __uint_as_float(~v[i].w);
    }
    __syncwarp();
#pragma unroll
    for (int o = 4; o < 32; o <<= 1) {
        s0 += __shfl_xor_sync(0xffffffffu, s0, o);
        s1 += __shfl_xor_sync(0xffffffffu, s1, o);
        s2 += __shfl_xor_sync(0xffffffffu, s2, o);
        s3 += __shfl_xor_sync(0xffffffffu, s3, o);
    }
    if (lane < 8) {
        const uint32_t w = (lane < 4) ? (bf16_bits(s0) | (bf16_bits(s2) << 16)) : (bf16_bits(s1) | (bf16_bits(s3) << 16));
        __nv_bfloat16* op = out + (idx >> 5) * (2 * D_MODEL) + br * D_MODEL + (idx & 31) * 16 + lane * 2;
        *reinterpret_cast<uint32_t*>(op) = w;
    }
}

__device__ __forceinline__ int chunk_of(int c) { return (c & 1) * (KCHUNKS / 2) + (c >> 1); }

__device__ __forceinline__ uint32_t* slot_ptr(int br, int idx, int lane) {
    return g_part + ((size_t)(br * 64 + idx) * 64) * 16 + (lane >> 2) * 16 + (lane & 3) * 4;
}

template <bool FUSED>
__global__ void __cluster_dims__(2, 1, 1) __launch_bounds__(NTHREADS, 1) fused_decode_kernel(const __grid_constant__ Params p) {
    extern __shared__ __align__(1024) unsigned char smem[];
    const uint32_t sbase = smem_u32(smem);
    const int cta = blockIdx.x;
    const int rank = cta & 1;
    const int br = cta >> 6;
    const int h = (cta >> 1) & 31;
    const int tid = threadIdx.x;
    const int warp = tid >> 5;
    const int lane = tid & 31;
    const uint32_t bar_full = sbase + SM_BARS;
    const uint32_t bar_empty = bar_full + NSTAGES * 8;
    const uint32_t bar_x = bar_empty + NSTAGES * 8;

    uint64_t pol;
    asm volatile("createpolicy.fractional.L2::evict_first.b64 %0, 1.0;" : "=l"(pol));

    if (warp == NCW) {
        const size_t kvoff = ((size_t)(rank * NH + h) * SK + (SK - WIN)) * DH;
        const char* kb = (const char*)(p.k[br] + kvoff);
        const char* vb = (const char*)(p.v[br] + kvoff);
        if (lane == 0) {
#pragma unroll
            for (int i = 0; i < NSTAGES; i++) {
                mbar_init(bar_full + i * 8, 1);
                mbar_init(bar_empty + i * 8, NCW);
            }
            mbar_init(bar_x, 1);
            mbar_init(bar_x + 8, 1);
            asm volatile("fence.mbarrier_init.release.cluster;" ::: "memory");
            asm volatile("fence.proxy.async.shared::cta;" ::: "memory");
            mbar_expect_tx(bar_x, 128 * 4);
            mbar_expect_tx(bar_x + 8, 64 * 4);
#pragma unroll
            for (int i = 0; i < MAX_INFLIGHT; i++) {
                mbar_expect_tx(bar_full + i * 8, CHUNK_BYTES);
                bulk_load(sbase + SM_RING + i * CHUNK_BYTES, kb + (size_t)chunk_of(i) * CHUNK_BYTES, CHUNK_BYTES,
                          bar_full + i * 8, pol);
            }
            asm volatile("prefetch.tensormap [%0];" ::"l"(&p.wo_map[br]) : "memory");
        }
        __syncwarp();
        asm volatile("barrier.cluster.arrive.relaxed.aligned;" ::: "memory");

        const int idx = cta & 63;
        uint32_t* slot = slot_ptr(br, idx, lane);
        uint32_t* done_ctr = g_ctr + br * 128;
        uint32_t* init_ctr = done_ctr + 64;
        uint32_t done_base = 0, init_base = 0;
        if (FUSED) {
            done_base = ld_relaxed(done_ctr) & ~63u;
            init_base = ld_relaxed(init_ctr) & ~63u;
#pragma unroll
            for (int i = 0; i < 8; i++)
                asm volatile("st.relaxed.gpu.global.v4.u32 [%0], {%1,%1,%1,%1};" ::"l"(slot + i * 8 * 16), "r"(0u) : "memory");
            __syncwarp();
            if (lane == 0) {
                asm volatile("fence.acq_rel.gpu;" ::: "memory");
                red_add1(init_ctr);
            }
        }
        if (lane == 0) {
            for (int i = MAX_INFLIGHT; i < 2 * KCHUNKS + WOCHUNKS; i++) {
                const int s = i % NSTAGES;
                if (FUSED && i == NSTAGES) {
                    for (int it = 0; ld_acquire(init_ctr) - init_base < 64u; it++)
                        if (it >= SPIN_LIMIT) __trap();
                }
                if (i >= NSTAGES) mbar_wait(bar_empty + s * 8, (i / NSTAGES - 1) & 1);
                {
                    const int n = i - MAX_INFLIGHT;
                    mbar_wait(bar_full + (n % NSTAGES) * 8, (n / NSTAGES) & 1);
                }
                if (i < 2 * KCHUNKS) {
                    const char* src = ((i < KCHUNKS) ? kb : vb) + (size_t)chunk_of(i & (KCHUNKS - 1)) * CHUNK_BYTES;
                    mbar_expect_tx(bar_full + s * 8, CHUNK_BYTES);
                    bulk_load(sbase + SM_RING + s * CHUNK_BYTES, src, CHUNK_BYTES, bar_full + s * 8, pol);
                } else {
                    constexpr int n = 2 * KCHUNKS - 1;
                    mbar_wait(bar_full + (n % NSTAGES) * 8, (n / NSTAGES) & 1);
                    mbar_expect_tx(bar_full + s * 8, CHUNK_BYTES);
#pragma unroll
                    for (int w = 0; w < 4; w++)
                        tensor_load_2d(sbase + SM_RING + s * CHUNK_BYTES + w * 8192, &p.wo_map[br],
                                       ((i - 2 * KCHUNKS) * 4 + w) * 64, h * DH + rank * 64, bar_full + s * 8, pol);
                }
            }
        }
        __syncwarp();
        asm volatile("barrier.cluster.wait.acquire.aligned;" ::: "memory");
        if (FUSED) {
            reduce_slots<true>(slot, p.out, br, idx, lane, done_ctr, done_base);
        }
        return;
    }

    const int g = lane >> 2;
    const int t = lane & 3;
    float* red = reinterpret_cast<float*>(smem + SM_RED);
    const uint32_t peer = rank ^ 1;

    {
        asm volatile("barrier.cluster.arrive.relaxed.aligned;" ::: "memory");
        const int rg = tid >> 4, cg = tid & 15;
        const int k0 = rank * 256 + rg * 16;
        const __nv_bfloat16* wp = p.wq[br] + (size_t)k0 * (NH * DH) + h * DH + cg * 8;
        uint4 w[16];
#pragma unroll
        for (int i = 0; i < 16; i++) w[i] = ldg_stream(wp + (size_t)i * (NH * DH), pol);
        uint4 xa[2][2];
#pragma unroll
        for (int b = 0; b < 2; b++) {
            const uint4* xp = reinterpret_cast<const uint4*>(p.x[br] + b * D_MODEL + k0);
            xa[b][0] = __ldg(xp);
            xa[b][1] = __ldg(xp + 1);
        }
        float acc[2][8];
#pragma unroll
        for (int j = 0; j < 8; j++) { acc[0][j] = 0.f; acc[1][j] = 0.f; }
#pragma unroll
        for (int i = 0; i < 16; i++) {
            float xv[2];
#pragma unroll
            for (int b = 0; b < 2; b++) {
                const uint4 q4 = xa[b][i >> 3];
                const int wi = (i >> 1) & 3;
                const uint32_t ww = wi == 0 ? q4.x : wi == 1 ? q4.y : wi == 2 ? q4.z : q4.w;
                xv[b] = (i & 1) ? bf_hi(ww) : bf_lo(ww);
            }
            const uint32_t ws[4] = {w[i].x, w[i].y, w[i].z, w[i].w};
#pragma unroll
            for (int j = 0; j < 4; j++) {
                const float lo = bf_lo(ws[j]), hi = bf_hi(ws[j]);
                acc[0][2 * j] = fmaf(xv[0], lo, acc[0][2 * j]);
                acc[0][2 * j + 1] = fmaf(xv[0], hi, acc[0][2 * j + 1]);
                acc[1][2 * j] = fmaf(xv[1], lo, acc[1][2 * j]);
                acc[1][2 * j + 1] = fmaf(xv[1], hi, acc[1][2 * j + 1]);
            }
        }
        const bool hi16 = lane >= 16;
        float mine[8];
#pragma unroll
        for (int j = 0; j < 8; j++) {
            const float send = hi16 ? acc[0][j] : acc[1][j];
            const float keep = hi16 ? acc[1][j] : acc[0][j];
            mine[j] = keep + __shfl_xor_sync(0xffffffffu, send, 16);
        }
        float4* dst = reinterpret_cast<float4*>(red + warp * 256 + (hi16 ? 128 : 0) + cg * 8);
        dst[0] = make_float4(mine[0], mine[1], mine[2], mine[3]);
        dst[1] = make_float4(mine[4], mine[5], mine[6], mine[7]);
        asm volatile("barrier.cluster.wait.acquire.aligned;" ::: "memory");
        consumer_bar();
        float s = 0.f;
#pragma unroll
        for (int ww = 0; ww < NCW; ww++) s += red[ww * 256 + tid];
        const int b = tid >> 7, col = tid & 127;
        if (b != rank) {
            st_async_u32(mapa(sbase + SM_QX + col * 4, peer), __float_as_uint(s), mapa(bar_x, peer));
        } else {
            mbar_wait_cluster(bar_x, 0);
            const float other = reinterpret_cast<const float*>(smem + SM_QX)[col];
            reinterpret_cast<__nv_bfloat16*>(smem + SM_QS)[col] = __float2bfloat16_rn(s + other);
        }
        consumer_bar();
    }

    uint32_t koff[4];
    uint4 qf[4];
#pragma unroll
    for (int j = 0; j < 4; j++) {
        koff[j] = (uint32_t)((4 * (j ^ (g & 1)) + t) * 16);
        qf[j] = lds128(sbase + SM_QS + koff[j]);
    }

    const int myz = t ^ (g >> 1);
    float sc[KCHUNKS / 4][2];
    {
        const uint32_t rowoff = (uint32_t)((warp * 16 + g) * ROW_BYTES);
#pragma unroll
        for (int c = 0; c < KCHUNKS; c++) {
            const int s = c % NSTAGES;
            mbar_wait(bar_full + s * 8, (c / NSTAGES) & 1);
            const uint32_t base = sbase + SM_RING + s * CHUNK_BYTES + (rowoff ^ (uint32_t)((c & 3) * 2 * ROW_BYTES));
            uint4 lo[4], hi[4];
#pragma unroll
            for (int j = 0; j < 4; j++) {
                lo[j] = lds128(base + koff[j]);
                hi[j] = lds128(base + 8 * ROW_BYTES + koff[j]);
            }
            float a0[4] = {0.f, 0.f, 0.f, 0.f}, a1[4] = {0.f, 0.f, 0.f, 0.f};
#pragma unroll
            for (int j = 0; j < 4; j++) {
                mma_bf16(a0, lo[j].x, hi[j].x, lo[j].y, hi[j].y, qf[j].x, qf[j].y);
                mma_bf16(a1, lo[j].z, hi[j].z, lo[j].w, hi[j].w, qf[j].z, qf[j].w);
            }
            __syncwarp();
            if (lane == 0) mbar_arrive(bar_empty + s * 8);
            const float r0 = (g & 1) ? (a0[1] + a1[1]) : (a0[0] + a1[0]);
            const float r1 = (g & 1) ? (a0[3] + a1[3]) : (a0[2] + a1[2]);
            if ((c & 3) == 0 || (c & 3) == myz) {
                sc[c >> 2][0] = r0;
                sc[c >> 2][1] = r1;
            }
        }
    }

    uint32_t pb[KCHUNKS / 4][2];
    {
        float* wmax = reinterpret_cast<float*>(smem + SM_WMAX);
        float* wsum = reinterpret_cast<float*>(smem + SM_WSUM);
        const float scale = 0.08838834764831845f;
#pragma unroll
        for (int c = 0; c < KCHUNKS / 4; c++) {
            sc[c][0] = bf16_round(bf16_round(sc[c][0]) * scale);
            sc[c][1] = bf16_round(bf16_round(sc[c][1]) * scale);
        }
        float m = sc[0][0];
#pragma unroll
        for (int c = 0; c < KCHUNKS / 4; c++) m = fmaxf(m, fmaxf(sc[c][0], sc[c][1]));
#pragma unroll
        for (int o = 1; o < 32; o <<= 1) m = fmaxf(m, __shfl_xor_sync(0xffffffffu, m, o));
        if (lane == 0) wmax[warp] = m;
        consumer_bar();
#pragma unroll
        for (int ww = 0; ww < NCW; ww++) m = fmaxf(m, wmax[ww]);
        const float LOG2E = 1.4426950408889634f;
        float sum = 0.f;
#pragma unroll
        for (int c = 0; c < KCHUNKS / 4; c++) {
            sc[c][0] = exp2f((sc[c][0] - m) * LOG2E);
            sc[c][1] = exp2f((sc[c][1] - m) * LOG2E);
            sum += sc[c][0] + sc[c][1];
        }
#pragma unroll
        for (int o = 1; o < 32; o <<= 1) sum += __shfl_xor_sync(0xffffffffu, sum, o);
        if (lane == 0) wsum[warp] = sum;
        consumer_bar();
        float tot = 0.f;
#pragma unroll
        for (int ww = 0; ww < NCW; ww++) tot += wsum[ww];
        const float inv = 1.0f / tot;
        const int sh = (g & 1) * 16;
#pragma unroll
        for (int c = 0; c < KCHUNKS / 4; c++) {
            pb[c][0] = bf16_bits(sc[c][0] * inv) << sh;
            pb[c][1] = bf16_bits(sc[c][1] * inv) << sh;
        }
    }

    float acc[8][4];
#pragma unroll
    for (int i = 0; i < 8; i++) { acc[i][0] = 0.f; acc[i][1] = 0.f; acc[i][2] = 0.f; acc[i][3] = 0.f; }
    const int mi = lane >> 3, r8 = lane & 7;
    {
        const uint32_t rowoff = (uint32_t)((warp * 16 + r8 + 8 * (mi >> 1)) * ROW_BYTES + (mi & 1) * 128);
        uint32_t voff[8];
#pragma unroll
        for (int i = 0; i < 8; i++) voff[i] = rowoff + (uint32_t)((i ^ r8) * 16);
#pragma unroll
        for (int c = 0; c < KCHUNKS; c++) {
            const int cc = KCHUNKS + c;
            const int s = cc % NSTAGES;
            mbar_wait(bar_full + s * 8, (cc / NSTAGES) & 1);
            const uint32_t base = sbase + SM_RING + s * CHUNK_BYTES;
            uint32_t a[8][4];
#pragma unroll
            for (int i = 0; i < 8; i++) ldsm_x4_trans(base + voff[i ^ ((c & 3) * 2)], a[i]);
            const uint32_t b0 = ((c & 3) == myz) ? pb[c >> 2][0] : 0u;
            const uint32_t b1 = ((c & 3) == myz) ? pb[c >> 2][1] : 0u;
#pragma unroll
            for (int i = 0; i < 8; i++) mma_bf16(acc[i], a[i][0], a[i][1], a[i][2], a[i][3], b0, b1);
            __syncwarp();
            if (lane == 0) mbar_arrive(bar_empty + s * 8);
        }
    }
    {
#pragma unroll
        for (int hf = 0; hf < 2; hf++) {
            float u[8];
#pragma unroll
            for (int i = 0; i < 8; i++) u[i] = acc[i][2 * hf] + acc[i ^ 1][2 * hf + 1];
            const float v0 = u[0] + __shfl_xor_sync(0xffffffffu, u[2], 1);
            const float v1 = u[1] + __shfl_xor_sync(0xffffffffu, u[3], 1);
            const float v4 = u[4] + __shfl_xor_sync(0xffffffffu, u[6], 1);
            const float v5 = u[5] + __shfl_xor_sync(0xffffffffu, u[7], 1);
            red[warp * 128 + hf * 64 + (2 * t) * 8 + g] = v0 + __shfl_xor_sync(0xffffffffu, v4, 2);
            red[warp * 128 + hf * 64 + (2 * t + 1) * 8 + g] = v1 + __shfl_xor_sync(0xffffffffu, v5, 2);
        }
        consumer_bar();
        if (tid < 128) {
            float s = 0.f;
#pragma unroll
            for (int ww = 0; ww < NCW; ww++) s += red[ww * 128 + tid];
            const uint32_t mine = bf16_bits(s);
            const uint32_t other = __shfl_down_sync(0xffffffffu, mine, 1);
            if ((tid & 1) == 0) {
                const int row = tid & 63;
                const uint32_t dst = (uint32_t)(tid >> 6);
                const uint32_t off = sbase + SM_OX + (uint32_t)((rank * 32 + ((row >> 1) & 3) * 8 + (row >> 3)) * 4);
                st_async_u32(mapa(off, dst), mine | (other << 16), mapa(bar_x + 8, dst));
            }
        }
    }

    {
        uint32_t a[4][4][4];
        {
            constexpr int cc0 = 2 * KCHUNKS, cc1 = 2 * KCHUNKS + 1;
            const int s = (warp < 4) ? (cc0 % NSTAGES) : (cc1 % NSTAGES);
            const uint32_t ph = (warp < 4) ? ((cc0 / NSTAGES) & 1) : ((cc1 / NSTAGES) & 1);
            mbar_wait(bar_full + s * 8, ph);
            const uint32_t base = sbase + SM_RING + s * CHUNK_BYTES + (warp & 3) * 8192 + (uint32_t)((r8 + 8 * (mi >> 1)) * 128);
#pragma unroll
            for (int ks = 0; ks < 4; ks++)
#pragma unroll
                for (int j = 0; j < 4; j++)
                    ldsm_x4_trans(base + (uint32_t)(ks * 16 * 128) + (uint32_t)(((2 * j + (mi & 1)) ^ r8) * 16), a[ks][j]);
        }
        mbar_wait_cluster(bar_x + 8, 0);
        const uint4 o0 = lds128(sbase + SM_OX + (uint32_t)(((g & 1) * 32 + t * 8) * 4));
        const uint4 o1 = lds128(sbase + SM_OX + (uint32_t)(((g & 1) * 32 + t * 8 + 4) * 4));
        const uint32_t ob[8] = {o0.x, o0.y, o0.z, o0.w, o1.x, o1.y, o1.z, o1.w};
        float e[4][4];
#pragma unroll
        for (int ks = 0; ks < 4; ks++) { e[ks][0] = 0.f; e[ks][1] = 0.f; e[ks][2] = 0.f; e[ks][3] = 0.f; }
#pragma unroll
        for (int j = 0; j < 4; j++) {
            const bool on = (g >> 1) == j;
#pragma unroll
            for (int ks = 0; ks < 4; ks++)
                mma_bf16(e[ks], a[ks][j][0], a[ks][j][1], a[ks][j][2], a[ks][j][3], on ? ob[2 * ks] : 0u,
                         on ? ob[2 * ks + 1] : 0u);
        }
        float f[4];
#pragma unroll
        for (int x = 0; x < 4; x++) f[x] = (e[0][x] + e[1][x]) + (e[2][x] + e[3][x]);
#pragma unroll
        for (int b = 0; b < 2; b++) {
            uint32_t* d = g_part + ((size_t)(br * 64 + b * 32 + warp * 4 + t) * 64 + (cta & 63)) * 16 + g * 2;
            asm volatile("st.relaxed.gpu.global.v2.u32 [%0], {%1,%2};" ::"l"(d), "r"(enc(f[b])), "r"(enc(f[2 + b])) : "memory");
        }
        if (FUSED && tid == 0) red_add1(g_ctr + br * 128);
    }
}

__global__ void __launch_bounds__(32) reduce_kernel(__nv_bfloat16* out) {
    const int br = blockIdx.x >> 6, idx = blockIdx.x & 63, lane = threadIdx.x;
    reduce_slots<false>(slot_ptr(br, idx, lane), out, br, idx, lane, nullptr, 0u);
}

typedef CUresult (*EncodeTiledFn)(CUtensorMap*, CUtensorMapDataType, cuuint32_t, void*, const cuuint64_t*, const cuuint64_t*,
                                  const cuuint32_t*, const cuuint32_t*, CUtensorMapInterleave, CUtensorMapSwizzle,
                                  CUtensorMapL2promotion, CUtensorMapFloatOOBfill);

}

extern "C" void kernel_launch(void* const* d_in, const int* in_sizes, int n_in, void* d_out, int out_size) {
    (void)in_sizes; (void)n_in; (void)out_size;
    static EncodeTiledFn encode = nullptr;
    static bool fused = true;
    if (!encode) {
        cudaFuncSetAttribute(fused_decode_kernel<true>, cudaFuncAttributeMaxDynamicSharedMemorySize, SM_TOTAL);
        cudaFuncSetAttribute(fused_decode_kernel<false>, cudaFuncAttributeMaxDynamicSharedMemorySize, SM_TOTAL);
        cudaLaunchConfig_t cfg = {};
        cfg.gridDim = dim3(NCTAS);
        cfg.blockDim = dim3(NTHREADS);
        cfg.dynamicSmemBytes = SM_TOTAL;
        cudaLaunchAttribute at[1];
        at[0].id = cudaLaunchAttributeClusterDimension;
        at[0].val.clusterDim.x = 2;
        at[0].val.clusterDim.y = 1;
        at[0].val.clusterDim.z = 1;
        cfg.attrs = at;
        cfg.numAttrs = 1;
        int nclusters = 0;
        if (cudaOccupancyMaxActiveClusters(&nclusters, fused_decode_kernel<true>, &cfg) == cudaSuccess)
            fused = nclusters >= NCTAS / 2;
        else
            (void)cudaGetLastError();
        void* fn = nullptr;
        cudaDriverEntryPointQueryResult qres;
        cudaGetDriverEntryPoint("cuTensorMapEncodeTiled", &fn, cudaEnableDefault, &qres);
        encode = (EncodeTiledFn)fn;
    }
    Params p;
    for (int i = 0; i < 2; i++) {
        p.x[i] = (const __nv_bfloat16*)d_in[5 * i + 0];
        p.k[i] = (const __nv_bfloat16*)d_in[5 * i + 1];
        p.v[i] = (const __nv_bfloat16*)d_in[5 * i + 2];
        p.wq[i] = (const __nv_bfloat16*)d_in[5 * i + 3];
        const cuuint64_t gdim[2] = {(cuuint64_t)D_MODEL, (cuuint64_t)(NH * DH)};
        const cuuint64_t gstride[1] = {(cuuint64_t)D_MODEL * 2};
        const cuuint32_t box[2] = {64u, 64u};
        const cuuint32_t estr[2] = {1u, 1u};
        encode(&p.wo_map[i], CU_TENSOR_MAP_DATA_TYPE_BFLOAT16, 2, d_in[5 * i + 4], gdim, gstride, box, estr,
               CU_TENSOR_MAP_INTERLEAVE_NONE, CU_TENSOR_MAP_SWIZZLE_128B, CU_TENSOR_MAP_L2_PROMOTION_L2_256B,
               CU_TENSOR_MAP_FLOAT_OOB_FILL_NONE);
    }
    p.out = (__nv_bfloat16*)d_out;
    if (fused) {
        fused_decode_kernel<true><<<NCTAS, NTHREADS, SM_TOTAL>>>(p);
    } else {
        fused_decode_kernel<false><<<NCTAS, NTHREADS, SM_TOTAL>>>(p);
        reduce_kernel<<<NCTAS, 32>>>((__nv_bfloat16*)d_out);
    }
}
```

```cpp
#include <cuda_runtime.h>
#include <cuda.h>
#include <cuda_bf16.h>
#include <stdint.h>

namespace {

constexpr int D_MODEL = 512;
constexpr int NH = 32;
constexpr int SK = 8192;
constexpr int DH = 128;
constexpr int WIN = 2048;
constexpr int ROW_BYTES = DH * 2;
constexpr int CHUNK_BYTES = 32768;
constexpr int NSTAGES = 6;
constexpr int MAX_INFLIGHT = 4;
constexpr int GATE_SLACK = 2;
constexpr int KCHUNKS = WIN * ROW_BYTES / CHUNK_BYTES;
constexpr int WOCHUNKS = 2;
constexpr int NCW = 8;
constexpr int NCT = NCW * 32;
constexpr int NTHREADS = NCT + 32;
constexpr int NCTAS = 128;
constexpr int SPIN_LIMIT = 1 << 22;

constexpr int SM_RING = 0;
constexpr int SM_RED = NSTAGES * CHUNK_BYTES;
constexpr int SM_QX = SM_RED + NCW * 256 * 4;
constexpr int SM_QS = SM_QX + 128 * 4;
constexpr int SM_OX = SM_QS + 128 * 2;
constexpr int SM_WMAX = SM_OX + 64 * 4;
constexpr int SM_WSUM = SM_WMAX + 32;
constexpr int SM_BARS = SM_WSUM + 32;
constexpr int SM_TOTAL = SM_BARS + (2 * NSTAGES + 2 + NCW) * 8;

struct Params {
    alignas(64) CUtensorMap wo_map[2];
    const __nv_bfloat16* x[2];
    const __nv_bfloat16* k[2];
    const __nv_bfloat16* v[2];
    const __nv_bfloat16* wq[2];
    __nv_bfloat16* out;
};

__device__ uint32_t g_part[2 * 64 * 64 * 16];
__device__ uint32_t g_ctr[2 * 128];

__device__ __forceinline__ uint32_t smem_u32(const void* p) { return (uint32_t)__cvta_generic_to_shared(p); }
__device__ __forceinline__ void mbar_init(uint32_t bar, uint32_t cnt) {
    asm volatile("mbarrier.init.shared::cta.b64 [%0], %1;" ::"r"(bar), "r"(cnt) : "memory");
}
__device__ __forceinline__ void mbar_expect_tx(uint32_t bar, uint32_t bytes) {
    asm volatile("mbarrier.arrive.expect_tx.shared::cta.b64 _, [%0], %1;" ::"r"(bar), "r"(bytes) : "memory");
}
__device__ __forceinline__ void mbar_arrive(uint32_t bar) {
    asm volatile("mbarrier.arrive.shared::cta.b64 _, [%0];" ::"r"(bar) : "memory");
}
__device__ __forceinline__ bool mbar_try(uint32_t bar, uint32_t parity) {
    uint32_t ok;
    asm volatile(
        "{\n"
        ".reg .pred p;\n"
        "mbarrier.try_wait.parity.shared::cta.b64 p, [%1], %2;\n"
        "selp.u32 %0, 1, 0, p;\n"
        "}\n"
        : "=r"(ok)
        : "r"(bar), "r"(parity)
        : "memory");
    return ok != 0;
}
__device__ __forceinline__ bool mbar_try_cluster(uint32_t bar, uint32_t parity) {
    uint32_t ok;
    asm volatile(
        "{\n"
        ".reg .pred p;\n"
        "mbarrier.try_wait.parity.acquire.cluster.shared::cta.b64 p, [%1], %2;\n"
        "selp.u32 %0, 1, 0, p;\n"
        "}\n"
        : "=r"(ok)
        : "r"(bar), "r"(parity)
        : "memory");
    return ok != 0;
}
__device__ __forceinline__ void mbar_wait(uint32_t bar, uint32_t parity) {
    if (mbar_try(bar, parity)) return;
#pragma unroll 1
    for (int i = 0; i < SPIN_LIMIT; i++)
        if (mbar_try(bar, parity)) return;
    __trap();
}
__device__ __forceinline__ void mbar_wait_cluster(uint32_t bar, uint32_t parity) {
#pragma unroll 1
    for (int i = 0; i < SPIN_LIMIT; i++)
        if (mbar_try_cluster(bar, parity)) return;
    __trap();
}
__device__ __forceinline__ void bulk_load(uint32_t dst, const void* src, uint32_t bytes, uint32_t bar, uint64_t pol) {
    asm volatile(
        "cp.async.bulk.shared::cluster.global.mbarrier::complete_tx::bytes.L2::cache_hint [%0], [%1], %2, [%3], %4;" ::"r"(dst),
        "l"(src), "r"(bytes), "r"(bar), "l"(pol)
        : "memory");
}
__device__ __forceinline__ void tensor_load_2d(uint32_t dst, const CUtensorMap* map, int c0, int c1, uint32_t bar,
                                               uint64_t pol) {
    asm volatile(
        "cp.async.bulk.tensor.2d.shared::cluster.global.tile.mbarrier::complete_tx::bytes.L2::cache_hint "
        "[%0], [%1, {%2, %3}], [%4], %5;" ::"r"(dst),
        "l"(map), "r"(c0), "r"(c1), "r"(bar), "l"(pol)
        : "memory");
}
__device__ __forceinline__ uint32_t mapa(uint32_t addr, uint32_t rank) {
    uint32_t r;
    asm volatile("mapa.shared::cluster.u32 %0, %1, %2;" : "=r"(r) : "r"(addr), "r"(rank));
    return r;
}
__device__ __forceinline__ void st_async_u32(uint32_t raddr, uint32_t v, uint32_t rbar) {
    asm volatile("st.async.shared::cluster.mbarrier::complete_tx::bytes.u32 [%0], %1, [%2];" ::"r"(raddr), "r"(v), "r"(rbar)
                 : "memory");
}
__device__ __forceinline__ void consumer_bar() { asm volatile("bar.sync 1, %0;" ::"n"(NCT) : "memory"); }
__device__ __forceinline__ uint4 lds128(uint32_t a) {
    uint4 v;
    asm volatile("ld.shared.v4.u32 {%0,%1,%2,%3}, [%4];" : "=r"(v.x), "=r"(v.y), "=r"(v.z), "=r"(v.w) : "r"(a));
    return v;
}
__device__ __forceinline__ void ldsm_x4_trans(uint32_t a, uint32_t (&r)[4]) {
    asm volatile("ldmatrix.sync.aligned.m8n8.x4.trans.shared.b16 {%0,%1,%2,%3}, [%4];"
                 : "=r"(r[0]), "=r"(r[1]), "=r"(r[2]), "=r"(r[3])
                 : "r"(a));
}
__device__ __forceinline__ void mma_bf16(float (&c)[4], uint32_t a0, uint32_t a1, uint32_t a2, uint32_t a3, uint32_t b0,
                                         uint32_t b1) {
    asm("mma.sync.aligned.m16n8k16.row.col.f32.bf16.bf16.f32 {%0,%1,%2,%3}, {%4,%5,%6,%7}, {%8,%9}, {%0,%1,%2,%3};"
        : "+f"(c[0]), "+f"(c[1]), "+f"(c[2]), "+f"(c[3])
        : "r"(a0), "r"(a1), "r"(a2), "r"(a3), "r"(b0), "r"(b1));
}
__device__ __forceinline__ uint4 ldg_stream(const void* p, uint64_t pol) {
    uint4 v;
    asm volatile("ld.global.nc.L1::no_allocate.L2::cache_hint.v4.u32 {%0,%1,%2,%3}, [%4], %5;"
                 : "=r"(v.x), "=r"(v.y), "=r"(v.z), "=r"(v.w)
                 : "l"(p), "l"(pol));
    return v;
}
__device__ __forceinline__ uint32_t ld_relaxed(const uint32_t* p) {
    uint32_t v;
    asm volatile("ld.relaxed.gpu.global.u32 %0, [%1];" : "=r"(v) : "l"(p) : "memory");
    return v;
}
__device__ __forceinline__ uint32_t ld_acquire(const uint32_t* p) {
    uint32_t v;
    asm volatile("ld.acquire.gpu.global.u32 %0, [%1];" : "=r"(v) : "l"(p) : "memory");
    return v;
}
__device__ __forceinline__ void red_add1(uint32_t* p) {
    asm volatile("red.relaxed.gpu.global.add.u32 [%0], 1;" ::"l"(p) : "memory");
}
__device__ __forceinline__ float bf_lo(uint32_t w) { return __uint_as_float(w << 16); }
__device__ __forceinline__ float bf_hi(uint32_t w) { return __uint_as_float(w & 0xffff0000u); }
__device__ __forceinline__ float bf16_round(float v) { return __bfloat162float(__float2bfloat16_rn(v)); }
__device__ __forceinline__ uint32_t bf16_bits(float v) { return (uint32_t)__bfloat16_as_ushort(__float2bfloat16_rn(v)); }
__device__ __forceinline__ uint32_t enc(float v) {
    uint32_t b = __float_as_uint(v);
    if (b == 0xffffffffu) b = 0x7fffffffu;
    return ~b;
}

template <bool POLL>
__device__ __forceinline__ void reduce_slots(const uint32_t* slot, __nv_bfloat16* out, int br, int idx, int lane,
                                             const uint32_t* ctr, uint32_t base) {
    uint4 v[8];
    uint32_t pending = 0xffu;
    uint32_t next = 32;
    for (int it = 0;; it++) {
        if (it >= SPIN_LIMIT) __trap();
        if (POLL && next < (uint32_t)(64 - GATE_SLACK + 1)) {
            uint32_t c = 0;
            if (lane == 0) c = ld_relaxed(ctr) - base;
            c = __shfl_sync(0xffffffffu, c, 0);
            if (c < next) continue;
            next = (c >= (uint32_t)(64 - GATE_SLACK)) ? 64u : min(c + (64u - c) / 2u, (uint32_t)(64 - GATE_SLACK));
        }
#pragma unroll
        for (int i = 0; i < 8; i++) {
            if (pending & (1u << i)) {
                asm volatile("ld.relaxed.gpu.global.v4.u32 {%0,%1,%2,%3}, [%4];"
                             : "=r"(v[i].x), "=r"(v[i].y), "=r"(v[i].z), "=r"(v[i].w)
                             : "l"(slot + i * 8 * 16)
                             : "memory");
            }
        }
#pragma unroll
        for (int i = 0; i < 8; i++) {
            if (!POLL || (v[i].x != 0u && v[i].y != 0u && v[i].z != 0u && v[i].w != 0u)) pending &= ~(1u << i);
        }
        if (__all_sync(0xffffffffu, pending == 0u)) break;
    }
    float s0 = 0.f, s1 = 0.f, s2 = 0.f, s3 = 0.f;
#pragma unroll
    for (int i = 0; i < 8; i++) {
        s0 += __uint_as_float(~v[i].x);
        s1 += __uint_as_float(~v[i].y);
        s2 += __uint_as_float(~v[i].z);
        s3 += __uint_as_float(~v[i].w);
    }
    __syncwarp();
#pragma unroll
    for (int o = 4; o < 32; o <<= 1) {
        s0 += __shfl_xor_sync(0xffffffffu, s0, o);
        s1 += __shfl_xor_sync(0xffffffffu, s1, o);
        s2 += __shfl_xor_sync(0xffffffffu, s2, o);
        s3 += __shfl_xor_sync(0xffffffffu, s3, o);
    }
    if (lane < 8) {
        const uint32_t w = (lane < 4) ? (bf16_bits(s0) | (bf16_bits(s2) << 16)) : (bf16_bits(s1) | (bf16_bits(s3) << 16));
        __nv_bfloat16* op = out + (idx >> 5) * (2 * D_MODEL) + br * D_MODEL + (idx & 31) * 16 + lane * 2;
        *reinterpret_cast<uint32_t*>(op) = w;
    }
}

__device__ __forceinline__ int chunk_of(int c) { return ((c >> 1) & 1) * (KCHUNKS / 2) + (c >> 2) * 2 + (c & 1); }

__device__ __forceinline__ uint32_t* slot_ptr(int br, int idx, int lane) {
    return g_part + ((size_t)(br * 64 + idx) * 64) * 16 + (lane >> 2) * 16 + (lane & 3) * 4;
}

template <bool FUSED>
__global__ void __cluster_dims__(2, 1, 1) __launch_bounds__(NTHREADS, 1) fused_decode_kernel(const __grid_constant__ Params p) {
    extern __shared__ __align__(1024) unsigned char smem[];
    const uint32_t sbase = smem_u32(smem);
    const int cta = blockIdx.x;
    const int rank = cta & 1;
    const int br = cta >> 6;
    const int h = (cta >> 1) & 31;
    const int tid = threadIdx.x;
    const int warp = tid >> 5;
    const int lane = tid & 31;
    const uint32_t bar_full = sbase + SM_BARS;
    const uint32_t bar_empty = bar_full + NSTAGES * 8;
    const uint32_t bar_x = bar_empty + NSTAGES * 8;
    const uint32_t bar_wo = bar_x + 2 * 8;

    uint64_t pol;
    asm volatile("createpolicy.fractional.L2::evict_first.b64 %0, 1.0;" : "=l"(pol));

    if (warp == NCW) {
        const size_t kvoff = ((size_t)(rank * NH + h) * SK + (SK - WIN)) * DH;
        const char* kb = (const char*)(p.k[br] + kvoff);
        const char* vb = (const char*)(p.v[br] + kvoff);
        if (lane == 0) {
#pragma unroll
            for (int i = 0; i < NSTAGES; i++) {
                mbar_init(bar_full + i * 8, 1);
                mbar_init(bar_empty + i * 8, NCW);
            }
            mbar_init(bar_x, 1);
            mbar_init(bar_x + 8, 1);
#pragma unroll
            for (int i = 0; i < NCW; i++) mbar_init(bar_wo + i * 8, 1);
            asm volatile("fence.mbarrier_init.release.cluster;" ::: "memory");
            asm volatile("fence.proxy.async.shared::cta;" ::: "memory");
            mbar_expect_tx(bar_x, 128 * 4);
            mbar_expect_tx(bar_x + 8, 64 * 4);
#pragma unroll
            for (int i = 0; i < MAX_INFLIGHT; i++) {
                mbar_expect_tx(bar_full + i * 8, CHUNK_BYTES);
                bulk_load(sbase + SM_RING + i * CHUNK_BYTES, kb + (size_t)chunk_of(i) * CHUNK_BYTES, CHUNK_BYTES,
                          bar_full + i * 8, pol);
            }
            asm volatile("prefetch.tensormap [%0];" ::"l"(&p.wo_map[br]) : "memory");
        }
        __syncwarp();
        asm volatile("barrier.cluster.arrive.relaxed.aligned;" ::: "memory");

        const int idx = cta & 63;
        uint32_t* slot = slot_ptr(br, idx, lane);
        uint32_t* done_ctr = g_ctr + br * 128;
        uint32_t* init_ctr = done_ctr + 64;
        uint32_t done_base = 0, init_base = 0;
        if (FUSED) {
            done_base = ld_relaxed(done_ctr) & ~63u;
            init_base = ld_relaxed(init_ctr) & ~63u;
#pragma unroll
            for (int i = 0; i < 8; i++)
                asm volatile("st.relaxed.gpu.global.v4.u32 [%0], {%1,%1,%1,%1};" ::"l"(slot + i * 8 * 16), "r"(0u) : "memory");
            __syncwarp();
            if (lane == 0) {
                asm volatile("fence.acq_rel.gpu;" ::: "memory");
                red_add1(init_ctr);
            }
        }
        if (lane == 0) {
            for (int i = MAX_INFLIGHT; i < 2 * KCHUNKS + WOCHUNKS; i++) {
                const int s = i % NSTAGES;
                if (FUSED && i == NSTAGES) {
                    for (int it = 0; ld_acquire(init_ctr) - init_base < 64u; it++)
                        if (it >= SPIN_LIMIT) __trap();
                }
                if (i >= NSTAGES) mbar_wait(bar_empty + s * 8, (i / NSTAGES - 1) & 1);
                {
                    const int n = i - MAX_INFLIGHT;
                    mbar_wait(bar_full + (n % NSTAGES) * 8, (n / NSTAGES) & 1);
                }
                if (i < 2 * KCHUNKS) {
                    const char* src = ((i < KCHUNKS) ? kb : vb) + (size_t)chunk_of(i & (KCHUNKS - 1)) * CHUNK_BYTES;
                    mbar_expect_tx(bar_full + s * 8, CHUNK_BYTES);
                    bulk_load(sbase + SM_RING + s * CHUNK_BYTES, src, CHUNK_BYTES, bar_full + s * 8, pol);
                } else {
                    constexpr int n = 2 * KCHUNKS - 1;
                    mbar_wait(bar_full + (n % NSTAGES) * 8, (n / NSTAGES) & 1);
#pragma unroll
                    for (int w = 0; w < 4; w++) {
                        const int cw = (i - 2 * KCHUNKS) * 4 + w;
                        mbar_expect_tx(bar_wo + cw * 8, 8192);
                        tensor_load_2d(sbase + SM_RING + s * CHUNK_BYTES + w * 8192, &p.wo_map[br], cw * 64,
                                       h * DH + rank * 64, bar_wo + cw * 8, pol);
                    }
                }
            }
        }
        __syncwarp();
        asm volatile("barrier.cluster.wait.acquire.aligned;" ::: "memory");
        if (FUSED) {
            reduce_slots<true>(slot, p.out, br, idx, lane, done_ctr, done_base);
        }
        return;
    }

    const int g = lane >> 2;
    const int t = lane & 3;
    float* red = reinterpret_cast<float*>(smem + SM_RED);
    const uint32_t peer = rank ^ 1;

    {
        asm volatile("barrier.cluster.arrive.relaxed.aligned;" ::: "memory");
        const int rg = tid >> 4, cg = tid & 15;
        const int k0 = rank * 256 + rg * 16;
        const __nv_bfloat16* wp = p.wq[br] + (size_t)k0 * (NH * DH) + h * DH + cg * 8;
        uint4 w[16];
#pragma unroll
        for (int i = 0; i < 16; i++) w[i] = ldg_stream(wp + (size_t)i * (NH * DH), pol);
        uint4 xa[2][2];
#pragma unroll
        for (int b = 0; b < 2; b++) {
            const uint4* xp = reinterpret_cast<const uint4*>(p.x[br] + b * D_MODEL + k0);
            xa[b][0] = __ldg(xp);
            xa[b][1] = __ldg(xp + 1);
        }
        float acc[2][8];
#pragma unroll
        for (int j = 0; j < 8; j++) { acc[0][j] = 0.f; acc[1][j] = 0.f; }
#pragma unroll
        for (int i = 0; i < 16; i++) {
            float xv[2];
#pragma unroll
            for (int b = 0; b < 2; b++) {
                const uint4 q4 = xa[b][i >> 3];
                const int wi = (i >> 1) & 3;
                const uint32_t ww = wi == 0 ? q4.x : wi == 1 ? q4.y : wi == 2 ? q4.z : q4.w;
                xv[b] = (i & 1) ? bf_hi(ww) : bf_lo(ww);
            }
            const uint32_t ws[4] = {w[i].x, w[i].y, w[i].z, w[i].w};
#pragma unroll
            for (int j = 0; j < 4; j++) {
                const float lo = bf_lo(ws[j]), hi = bf_hi(ws[j]);
                acc[0][2 * j] = fmaf(xv[0], lo, acc[0][2 * j]);
                acc[0][2 * j + 1] = fmaf(xv[0], hi, acc[0][2 * j + 1]);
                acc[1][2 * j] = fmaf(xv[1], lo, acc[1][2 * j]);
                acc[1][2 * j + 1] = fmaf(xv[1], hi, acc[1][2 * j + 1]);
            }
        }
        const bool hi16 = lane >= 16;
        float mine[8];
#pragma unroll
        for (int j = 0; j < 8; j++) {
            const float send = hi16 ? acc[0][j] : acc[1][j];
            const float keep = hi16 ? acc[1][j] : acc[0][j];
            mine[j] = keep + __shfl_xor_sync(0xffffffffu, send, 16);
        }
        float4* dst = reinterpret_cast<float4*>(red + warp * 256 + (hi16 ? 128 : 0) + cg * 8);
        dst[0] = make_float4(mine[0], mine[1], mine[2], mine[3]);
        dst[1] = make_float4(mine[4], mine[5], mine[6], mine[7]);
        asm volatile("barrier.cluster.wait.acquire.aligned;" ::: "memory");
        consumer_bar();
        float s = 0.f;
#pragma unroll
        for (int ww = 0; ww < NCW; ww++) s += red[ww * 256 + tid];
        const int b = tid >> 7, col = tid & 127;
        if (b != rank) {
            st_async_u32(mapa(sbase + SM_QX + col * 4, peer), __float_as_uint(s), mapa(bar_x, peer));
        } else {
            mbar_wait_cluster(bar_x, 0);
            const float other = reinterpret_cast<const float*>(smem + SM_QX)[col];
            reinterpret_cast<__nv_bfloat16*>(smem + SM_QS)[col] = __float2bfloat16_rn(s + other);
        }
        consumer_bar();
    }

    uint32_t koff[4];
    uint4 qf[4];
#pragma unroll
    for (int j = 0; j < 4; j++) {
        koff[j] = (uint32_t)((4 * (j ^ (g & 1)) + t) * 16);
        qf[j] = lds128(sbase + SM_QS + koff[j]);
    }

    const int myz = t ^ (g >> 1);
    float sc[KCHUNKS / 4][2];
    {
        const uint32_t rowoff = (uint32_t)((warp * 16 + g) * ROW_BYTES);
#pragma unroll
        for (int c = 0; c < KCHUNKS; c++) {
            const int s = c % NSTAGES;
            mbar_wait(bar_full + s * 8, (c / NSTAGES) & 1);
            const uint32_t base = sbase + SM_RING + s * CHUNK_BYTES + (rowoff ^ (uint32_t)((c & 3) * 2 * ROW_BYTES));
            uint4 lo[4], hi[4];
#pragma unroll
            for (int j = 0; j < 4; j++) {
                lo[j] = lds128(base + koff[j]);
                hi[j] = lds128(base + 8 * ROW_BYTES + koff[j]);
            }
            float a0[4] = {0.f, 0.f, 0.f, 0.f}, a1[4] = {0.f, 0.f, 0.f, 0.f};
#pragma unroll
            for (int j = 0; j < 4; j++) {
                mma_bf16(a0, lo[j].x, hi[j].x, lo[j].y, hi[j].y, qf[j].x, qf[j].y);
                mma_bf16(a1, lo[j].z, hi[j].z, lo[j].w, hi[j].w, qf[j].z, qf[j].w);
            }
            __syncwarp();
            if (lane == 0) mbar_arrive(bar_empty + s * 8);
            const float r0 = (g & 1) ? (a0[1] + a1[1]) : (a0[0] + a1[0]);
            const float r1 = (g & 1) ? (a0[3] + a1[3]) : (a0[2] + a1[2]);
            if ((c & 3) == 0 || (c & 3) == myz) {
                sc[c >> 2][0] = r0;
                sc[c >> 2][1] = r1;
            }
        }
    }

    uint32_t pb[KCHUNKS / 4][2];
    {
        float* wmax = reinterpret_cast<float*>(smem + SM_WMAX);
        float* wsum = reinterpret_cast<float*>(smem + SM_WSUM);
        const float scale = 0.08838834764831845f;
#pragma unroll
        for (int c = 0; c < KCHUNKS / 4; c++) {
            sc[c][0] = bf16_round(bf16_round(sc[c][0]) * scale);
            sc[c][1] = bf16_round(bf16_round(sc[c][1]) * scale);
        }
        float m = sc[0][0];
#pragma unroll
        for (int c = 0; c < KCHUNKS / 4; c++) m = fmaxf(m, fmaxf(sc[c][0], sc[c][1]));
#pragma unroll
        for (int o = 1; o < 32; o <<= 1) m = fmaxf(m, __shfl_xor_sync(0xffffffffu, m, o));
        if (lane == 0) wmax[warp] = m;
        consumer_bar();
#pragma unroll
        for (int ww = 0; ww < NCW; ww++) m = fmaxf(m, wmax[ww]);
        const float LOG2E = 1.4426950408889634f;
        float sum = 0.f;
#pragma unroll
        for (int c = 0; c < KCHUNKS / 4; c++) {
            sc[c][0] = exp2f((sc[c][0] - m) * LOG2E);
            sc[c][1] = exp2f((sc[c][1] - m) * LOG2E);
            sum += sc[c][0] + sc[c][1];
        }
#pragma unroll
        for (int o = 1; o < 32; o <<= 1) sum += __shfl_xor_sync(0xffffffffu, sum, o);
        if (lane == 0) wsum[warp] = sum;
        consumer_bar();
        float tot = 0.f;
#pragma unroll
        for (int ww = 0; ww < NCW; ww++) tot += wsum[ww];
        const float inv = 1.0f / tot;
        const int sh = (g & 1) * 16;
#pragma unroll
        for (int c = 0; c < KCHUNKS / 4; c++) {
            pb[c][0] = bf16_bits(sc[c][0] * inv) << sh;
            pb[c][1] = bf16_bits(sc[c][1] * inv) << sh;
        }
    }

    float acc[8][4];
#pragma unroll
    for (int i = 0; i < 8; i++) { acc[i][0] = 0.f; acc[i][1] = 0.f; acc[i][2] = 0.f; acc[i][3] = 0.f; }
    const int mi = lane >> 3, r8 = lane & 7;
    {
        const uint32_t rowoff = (uint32_t)((warp * 16 + r8 + 8 * (mi >> 1)) * ROW_BYTES + (mi & 1) * 128);
        uint32_t voff[8];
#pragma unroll
        for (int i = 0; i < 8; i++) voff[i] = rowoff + (uint32_t)((i ^ r8) * 16);
#pragma unroll
        for (int c = 0; c < KCHUNKS; c++) {
            const int cc = KCHUNKS + c;
            const int s = cc % NSTAGES;
            mbar_wait(bar_full + s * 8, (cc / NSTAGES) & 1);
            const uint32_t base = sbase + SM_RING + s * CHUNK_BYTES;
            uint32_t a[8][4];
#pragma unroll
            for (int i = 0; i < 8; i++) ldsm_x4_trans(base + voff[i ^ ((c & 3) * 2)], a[i]);
            const uint32_t b0 = ((c & 3) == myz) ? pb[c >> 2][0] : 0u;
            const uint32_t b1 = ((c & 3) == myz) ? pb[c >> 2][1] : 0u;
#pragma unroll
            for (int i = 0; i < 8; i++) mma_bf16(acc[i], a[i][0], a[i][1], a[i][2], a[i][3], b0, b1);
            __syncwarp();
            if (lane == 0) mbar_arrive(bar_empty + s * 8);
        }
    }
    {
#pragma unroll
        for (int hf = 0; hf < 2; hf++) {
            float u[8];
#pragma unroll
            for (int i = 0; i < 8; i++) u[i] = acc[i][2 * hf] + acc[i ^ 1][2 * hf + 1];
            const float v0 = u[0] + __shfl_xor_sync(0xffffffffu, u[2], 1);
            const float v1 = u[1] + __shfl_xor_sync(0xffffffffu, u[3], 1);
            const float v4 = u[4] + __shfl_xor_sync(0xffffffffu, u[6], 1);
            const float v5 = u[5] + __shfl_xor_sync(0xffffffffu, u[7], 1);
            red[warp * 128 + hf * 64 + (2 * t) * 8 + g] = v0 + __shfl_xor_sync(0xffffffffu, v4, 2);
            red[warp * 128 + hf * 64 + (2 * t + 1) * 8 + g] = v1 + __shfl_xor_sync(0xffffffffu, v5, 2);
        }
        consumer_bar();
        if (tid < 128) {
            float s = 0.f;
#pragma unroll
            for (int ww = 0; ww < NCW; ww++) s += red[ww * 128 + tid];
            const uint32_t mine = bf16_bits(s);
            const uint32_t other = __shfl_down_sync(0xffffffffu, mine, 1);
            if ((tid & 1) == 0) {
                const int row = tid & 63;
                const uint32_t dst = (uint32_t)(tid >> 6);
                const uint32_t off = sbase + SM_OX + (uint32_t)((rank * 32 + ((row >> 1) & 3) * 8 + (row >> 3)) * 4);
                st_async_u32(mapa(off, dst), mine | (other << 16), mapa(bar_x + 8, dst));
            }
        }
    }

    {
        mbar_wait_cluster(bar_x + 8, 0);
        const uint4 o0 = lds128(sbase + SM_OX + (uint32_t)(((g & 1) * 32 + t * 8) * 4));
        const uint4 o1 = lds128(sbase + SM_OX + (uint32_t)(((g & 1) * 32 + t * 8 + 4) * 4));
        const uint32_t ob[8] = {o0.x, o0.y, o0.z, o0.w, o1.x, o1.y, o1.z, o1.w};
        constexpr int cc0 = 2 * KCHUNKS, cc1 = 2 * KCHUNKS + 1;
        const int s = (warp < 4) ? (cc0 % NSTAGES) : (cc1 % NSTAGES);
        const uint32_t base = sbase + SM_RING + s * CHUNK_BYTES + (warp & 3) * 8192 + (uint32_t)((r8 + 8 * (mi >> 1)) * 128);
        mbar_wait(bar_wo + warp * 8, 0);
        float e[4][4];
#pragma unroll
        for (int ks = 0; ks < 4; ks++) {
            uint32_t a[4][4];
#pragma unroll
            for (int j = 0; j < 4; j++)
                ldsm_x4_trans(base + (uint32_t)(ks * 16 * 128) + (uint32_t)(((2 * j + (mi & 1)) ^ r8) * 16), a[j]);
            e[ks][0] = 0.f; e[ks][1] = 0.f; e[ks][2] = 0.f; e[ks][3] = 0.f;
#pragma unroll
            for (int j = 0; j < 4; j++) {
                const bool on = (g >> 1) == j;
                mma_bf16(e[ks], a[j][0], a[j][1], a[j][2], a[j][3], on ? ob[2 * ks] : 0u, on ? ob[2 * ks + 1] : 0u);
            }
        }
        float f[4];
#pragma unroll
        for (int x = 0; x < 4; x++) f[x] = (e[0][x] + e[1][x]) + (e[2][x] + e[3][x]);
#pragma unroll
        for (int b = 0; b < 2; b++) {
            uint32_t* d = g_part + ((size_t)(br * 64 + b * 32 + warp * 4 + t) * 64 + (cta & 63)) * 16 + g * 2;
            asm volatile("st.relaxed.gpu.global.v2.u32 [%0], {%1,%2};" ::"l"(d), "r"(enc(f[b])), "r"(enc(f[2 + b])) : "memory");
        }
        if (FUSED && tid == 0) red_add1(g_ctr + br * 128);
    }
}

__global__ void __launch_bounds__(32) reduce_kernel(__nv_bfloat16* out) {
    const int br = blockIdx.x >> 6, idx = blockIdx.x & 63, lane = threadIdx.x;
    reduce_slots<false>(slot_ptr(br, idx, lane), out, br, idx, lane, nullptr, 0u);
}

typedef CUresult (*EncodeTiledFn)(CUtensorMap*, CUtensorMapDataType, cuuint32_t, void*, const cuuint64_t*, const cuuint64_t*,
                                  const cuuint32_t*, const cuuint32_t*, CUtensorMapInterleave, CUtensorMapSwizzle,
                                  CUtensorMapL2promotion, CUtensorMapFloatOOBfill);

}

extern "C" void kernel_launch(void* const* d_in, const int* in_sizes, int n_in, void* d_out, int out_size) {
    (void)in_sizes; (void)n_in; (void)out_size;
    static EncodeTiledFn encode = nullptr;
    static bool fused = true;
    if (!encode) {
        cudaFuncSetAttribute(fused_decode_kernel<true>, cudaFuncAttributeMaxDynamicSharedMemorySize, SM_TOTAL);
        cudaFuncSetAttribute(fused_decode_kernel<false>, cudaFuncAttributeMaxDynamicSharedMemorySize, SM_TOTAL);
        cudaLaunchConfig_t cfg = {};
        cfg.gridDim = dim3(NCTAS);
        cfg.blockDim = dim3(NTHREADS);
        cfg.dynamicSmemBytes = SM_TOTAL;
        cudaLaunchAttribute at[1];
        at[0].id = cudaLaunchAttributeClusterDimension;
        at[0].val.clusterDim.x = 2;
        at[0].val.clusterDim.y = 1;
        at[0].val.clusterDim.z = 1;
        cfg.attrs = at;
        cfg.numAttrs = 1;
        int nclusters = 0;
        if (cudaOccupancyMaxActiveClusters(&nclusters, fused_decode_kernel<true>, &cfg) == cudaSuccess)
            fused = nclusters >= NCTAS / 2;
        else
            (void)cudaGetLastError();
        void* fn = nullptr;
        cudaDriverEntryPointQueryResult qres;
        cudaGetDriverEntryPoint("cuTensorMapEncodeTiled", &fn, cudaEnableDefault, &qres);
        encode = (EncodeTiledFn)fn;
    }
    Params p;
    for (int i = 0; i < 2; i++) {
        p.x[i] = (const __nv_bfloat16*)d_in[5 * i + 0];
        p.k[i] = (const __nv_bfloat16*)d_in[5 * i + 1];
        p.v[i] = (const __nv_bfloat16*)d_in[5 * i + 2];
        p.wq[i] = (const __nv_bfloat16*)d_in[5 * i + 3];
        const cuuint64_t gdim[2] = {(cuuint64_t)D_MODEL, (cuuint64_t)(NH * DH)};
        const cuuint64_t gstride[1] = {(cuuint64_t)D_MODEL * 2};
        const cuuint32_t box[2] = {64u, 64u};
        const cuuint32_t estr[2] = {1u, 1u};
        encode(&p.wo_map[i], CU_TENSOR_MAP_DATA_TYPE_BFLOAT16, 2, d_in[5 * i + 4], gdim, gstride, box, estr,
               CU_TENSOR_MAP_INTERLEAVE_NONE, CU_TENSOR_MAP_SWIZZLE_128B, CU_TENSOR_MAP_L2_PROMOTION_L2_256B,
               CU_TENSOR_MAP_FLOAT_OOB_FILL_NONE);
    }
    p.out = (__nv_bfloat16*)d_out;
    if (fused) {
        fused_decode_kernel<true><<<NCTAS, NTHREADS, SM_TOTAL>>>(p);
    } else {
        fused_decode_kernel<false><<<NCTAS, NTHREADS, SM_TOTAL>>>(p);
        reduce_kernel<<<NCTAS, 32>>>((__nv_bfloat16*)d_out);
    }
}
```
